```python
import torch

def _softmax(x, axis=-1):
    return torch.softmax(x, dim=axis)

def _gelu(x):
    return torch.nn.functional.gelu(x, approximate='tanh')

def _silu(x):
    return torch.nn.functional.silu(x)

def _sigmoid(x):
    return torch.sigmoid(x)

def _layernorm(x, axis=-1, eps=1e-05):
    m = x.mean(dim=axis, keepdim=True)
    v = x.var(dim=axis, keepdim=True, unbiased=False)
    return (x - m) / torch.sqrt(v + eps)

def _scatter_add(tgt, idx, src, axis=0):
    return tgt.clone().index_add_(axis, idx, src)

def _segment_sum(src, seg, n):
    out = torch.zeros((n,) + src.shape[1:], dtype=src.dtype)
    return out.index_add_(0, seg, src)

def _pad(x, pw):
    flat = tuple((v for pair in reversed(pw) for v in pair))
    return torch.nn.functional.pad(x, flat)
kernel_name = 'gated_mix__memory_aug_recurrent_mem_tr__sliding_local_dilated__prompt'

def setup_inputs():

    _w = lambda a: (lambda t: t.to(torch.bfloat16) if t.is_floating_point() else t)(torch.as_tensor(a))

    def _A_setup():
        B, S, Dm = (1, 2048, 640)
        H, Dh = (32, 192)
        M, seg = (8, 32)
        seg = min(seg, S)
        S = S // seg * seg
        return {'x': _w((lambda *s: torch.randn(*s, dtype=torch.bfloat16) * 0.05)(B, S, Dm)), 'mem0': _w((lambda *s: torch.randn(*s, dtype=torch.bfloat16) * 1.6)(B, M, Dm)), 'Wq': _w((lambda *s: torch.randn(*s, dtype=torch.bfloat16) * 0.8)(Dm, H, Dh) * Dm ** (-0.5)), 'Wk': _w((lambda *s: torch.randn(*s, dtype=torch.bfloat16) * 0.8)(Dm, H, Dh) * Dm ** (-0.5)), 'Wv': _w((lambda *s: torch.randn(*s, dtype=torch.bfloat16) * 1.6)(Dm, H, Dh) * Dm ** (-0.5)), 'Wo': _w((lambda *s: torch.randn(*s, dtype=torch.bfloat16) * 1.6)(H, Dh, Dm) * (H * Dh) ** (-0.5)), 'seg_len': seg}
    _A_in = _A_setup()

    def _B_setup():
        B, S, D = (1, 2048, 640)
        return {'x': _w((lambda *s: torch.randn(*s, dtype=torch.bfloat16) * 0.05)(B, S, D)), 'wqkv': _w((lambda *s: torch.randn(*s, dtype=torch.bfloat16) * 0.8)(D, 3 * D)), 'wo': _w((lambda *s: torch.randn(*s, dtype=torch.bfloat16) * 0.05)(D, D))}
    _B_in = _B_setup()
    return {'A_x': _A_in['x'], 'A_mem0': _A_in['mem0'], 'A_Wq': _A_in['Wq'], 'A_Wk': _A_in['Wk'], 'A_Wv': _A_in['Wv'], 'A_Wo': _A_in['Wo'], 'A_seg_len': _A_in['seg_len'], 'B_x': _B_in['x'], 'B_wqkv': _B_in['wqkv'], 'B_wo': _B_in['wo'], 'gate_w': _w((lambda *s: torch.randn(*s, dtype=torch.bfloat16) * 0.05)(640) * 16.0)}

def reference(A_x, A_mem0, A_Wq, A_Wk, A_Wv, A_Wo, A_seg_len, B_x, B_wqkv, B_wo, gate_w):

    def _A_ref(x, mem0, Wq, Wk, Wv, Wo, seg_len):
        B, S, Dm = x.shape
        H, Dh = (Wq.shape[1], Wq.shape[2])
        M = mem0.shape[1]
        scale = Dh ** (-0.5)
        n_seg = S // seg_len
        L = M + seg_len
        idx = torch.arange(L)
        mask = (idx[:, None] < M) | (idx[:, None] >= idx[None, :])
        mem = mem0
        outs = []
        for s in range(n_seg):
            xs = x[:, s * seg_len:(s + 1) * seg_len, :].clone()
            h = torch.concatenate([mem, xs], axis=1)
            q = torch.einsum('btd,dhe->bhte', h, Wq)
            k = torch.einsum('btd,dhe->bhte', h, Wk)
            v = torch.einsum('btd,dhe->bhte', h, Wv)
            scores = torch.einsum('bhqe,bhke->bhqk', q, k) * scale
            scores = torch.where(mask[None, None], scores, -1000000000.0)
            p = _softmax(scores, axis=-1)
            o = torch.einsum('bhqk,bhke->bhqe', p, v)
            o = torch.einsum('bhte,hed->btd', o, Wo)
            mem = o[:, :M, :].clone()
            outs.append(o[:, M:, :])
        return torch.concatenate(outs, axis=1)

    def _B_ref(x, wqkv, wo):
        B, S, D = x.shape
        H = 32
        Dh = D // H
        W, dil = (8, 2)
        qkv = (lambda x, *d: x.permute(*d))((x @ wqkv).reshape(B, S, 3, H, Dh), 2, 0, 3, 1, 4)
        q, k, v = (qkv[0], qkv[1], qkv[2])
        scale = Dh ** (-0.5)
        pos = torch.arange(S)
        off = torch.arange(W) * dil
        idx = pos[:, None] - off[None, :]
        mask = idx >= 0
        idx_c = torch.where(mask, idx, 0).reshape(-1)
        kg = k[:, :, idx_c, :].reshape(B, H, S, W, Dh)
        vg = v[:, :, idx_c, :].reshape(B, H, S, W, Dh)
        logits = torch.einsum('bhsd,bhswd->bhsw', q, kg) * scale
        logits = torch.where(mask[None, None, :, :], logits, -1000000000.0)
        attn = _softmax(logits, axis=-1)
        o = torch.einsum('bhsw,bhswd->bhsd', attn, vg)
        return (lambda x, *d: x.permute(*d))(o, 0, 2, 1, 3).reshape(B, S, D) @ wo
    x = A_x
    g = _sigmoid((x * gate_w).sum(-1, keepdims=True))
    a = _A_ref(x, A_mem0, A_Wq, A_Wk, A_Wv, A_Wo, A_seg_len)
    b = _B_ref(x, B_wqkv, B_wo)
    return g * a + (1 - g) * b
```

```cpp
#include <cuda_runtime.h>
#include <cuda_bf16.h>
#include <cuda.h>
#include <stdint.h>
#include <stddef.h>

typedef __nv_bfloat16 bf16;

constexpr int S_LEN = 2048, DM = 640, NH = 32, DH = 192, HD = NH * DH;
constexpr int NSEG = 64;
constexpr int NCTA = 96, NRED = 80;
constexpr int SPIN_MAX = 1 << 22;

__device__ bf16 g_oA[S_LEN * HD];
__device__ bf16 g_Qp[256 * HD];
__device__ __align__(128) char g_kv[(size_t)NSEG * NCTA * 10240];
__device__ bf16 g_qkvB[S_LEN * 3 * DM];
__device__ bf16 g_oB[S_LEN * DM];
__device__ float g_gate[S_LEN];
__device__ char g_rs_raw[4 << 20];
__device__ unsigned g_side[NCTA * 8];
__device__ unsigned g_err;
struct AuxCtl {
    unsigned seg[32];
    unsigned ata[32];
    unsigned at[16], b1[16];
    unsigned qp[32];
    unsigned fin[160];
    unsigned next, pad[31];
};
__device__ __align__(128) AuxCtl g_ctl;
__device__ bf16 g_part[96 * 128 * DM];

__device__ __forceinline__ uint32_t smem_u32(const void* p) { return (uint32_t)__cvta_generic_to_shared(p); }
__device__ __forceinline__ uint32_t mapa(uint32_t addr, uint32_t rank) {
    uint32_t r; asm volatile("mapa.shared::cluster.u32 %0, %1, %2;" : "=r"(r) : "r"(addr), "r"(rank)); return r;
}
__device__ __forceinline__ void mbar_init(uint32_t bar, uint32_t cnt) {
    asm volatile("mbarrier.init.shared::cta.b64 [%0], %1;" :: "r"(bar), "r"(cnt) : "memory");
}
__device__ __forceinline__ void mbar_expect(uint32_t bar, uint32_t bytes) {
    asm volatile("mbarrier.arrive.expect_tx.shared::cta.b64 _, [%0], %1;" :: "r"(bar), "r"(bytes) : "memory");
}
__device__ __forceinline__ void mbar_arrive(uint32_t bar) {
    asm volatile("mbarrier.arrive.shared::cta.b64 _, [%0];" :: "r"(bar) : "memory");
}
__device__ __forceinline__ bool mbar_try_cluster(uint32_t bar, uint32_t parity) {
    uint32_t ok;
    asm volatile("{\n.reg .pred p;\nmbarrier.try_wait.parity.acquire.cluster.shared::cta.b64 p, [%1], %2;\nselp.u32 %0, 1, 0, p;\n}"
                 : "=r"(ok) : "r"(bar), "r"(parity) : "memory");
    return ok;
}
__device__ __forceinline__ void mbar_wait(uint32_t bar, uint32_t parity) {
    asm volatile("{\n.reg .pred p;\n.reg .u32 n;\nmov.u32 n, 0;\n"
                 "MW_L_%=:\nmbarrier.try_wait.parity.shared::cta.b64 p, [%0], %1;\n@p bra.uni MW_D_%=;\n"
                 "add.u32 n, n, 1;\nsetp.lt.u32 p, n, %2;\n@p bra.uni MW_L_%=;\n"
                 "st.global.u32 [%3], 1;\nMW_D_%=:\n}"
                 :: "r"(bar), "r"(parity), "n"(SPIN_MAX), "l"(&g_err) : "memory");
}
__device__ __forceinline__ bool elect_one() {
    uint32_t pred;
    asm volatile("{\n.reg .pred P;\nelect.sync _|P, 0xffffffff;\nselp.b32 %0, 1, 0, P;\n}" : "=r"(pred));
    return pred != 0;
}
__device__ __forceinline__ void tma2d(uint32_t dst, const CUtensorMap* tm, int c0, int c1, uint32_t bar) {
    asm volatile("cp.async.bulk.tensor.2d.shared::cluster.global.mbarrier::complete_tx::bytes [%0], [%1, {%3, %4}], [%2];"
                 :: "r"(dst), "l"(tm), "r"(bar), "r"(c0), "r"(c1) : "memory");
}
__device__ __forceinline__ void tma2d_prefetch(const CUtensorMap* tm, int c0, int c1) {
    asm volatile("cp.async.bulk.prefetch.tensor.2d.L2.global [%0, {%1, %2}];" :: "l"(tm), "r"(c0), "r"(c1) : "memory");
}
__device__ __forceinline__ void bar_sync(int id, int n) { asm volatile("barrier.sync %0, %1;" :: "r"(id), "r"(n) : "memory"); }
__device__ __forceinline__ void bar_sync_dep(int id, int n, uint32_t dep) {
    asm volatile("{ .reg .u32 t; min.u32 t, %2, %1; max.u32 t, t, %1; barrier.sync %0, t; }" :: "r"(id), "r"(n), "r"(dep) : "memory");
}
__device__ __forceinline__ void bar_arrive_dep(int id, int n, uint32_t dep) {
    asm volatile("{ .reg .u32 t; min.u32 t, %2, %1; max.u32 t, t, %1; barrier.arrive %0, t; }" :: "r"(id), "r"(n), "r"(dep) : "memory");
}
__device__ __forceinline__ void bar_arrive(int id, int n) { asm volatile("barrier.arrive %0, %1;" :: "r"(id), "r"(n) : "memory"); }
__device__ __forceinline__ void fence_async_smem() { asm volatile("fence.proxy.async.shared::cta;" ::: "memory"); }
__device__ __forceinline__ void cluster_sync() {
    asm volatile("barrier.cluster.arrive.release;\nbarrier.cluster.wait.acquire;" ::: "memory");
}
__device__ __forceinline__ void ldsm4(uint32_t& r0, uint32_t& r1, uint32_t& r2, uint32_t& r3, uint32_t a) {
    asm volatile("ldmatrix.sync.aligned.m8n8.x4.shared.b16 {%0,%1,%2,%3}, [%4];" : "=r"(r0), "=r"(r1), "=r"(r2), "=r"(r3) : "r"(a) : "memory");
}
__device__ __forceinline__ void ldsm4t(uint32_t& r0, uint32_t& r1, uint32_t& r2, uint32_t& r3, uint32_t a) {
    asm volatile("ldmatrix.sync.aligned.m8n8.x4.trans.shared.b16 {%0,%1,%2,%3}, [%4];" : "=r"(r0), "=r"(r1), "=r"(r2), "=r"(r3) : "r"(a) : "memory");
}
__device__ __forceinline__ void ldsm2t(uint32_t& r0, uint32_t& r1, uint32_t a) {
    asm volatile("ldmatrix.sync.aligned.m8n8.x2.trans.shared.b16 {%0,%1}, [%2];" : "=r"(r0), "=r"(r1) : "r"(a) : "memory");
}
__device__ __forceinline__ void ldsm2(uint32_t& r0, uint32_t& r1, uint32_t a) {
    asm volatile("ldmatrix.sync.aligned.m8n8.x2.shared.b16 {%0,%1}, [%2];" : "=r"(r0), "=r"(r1) : "r"(a) : "memory");
}
__device__ __forceinline__ void bulk_g2s(uint32_t dst, const void* src, uint32_t bytes, uint32_t bar) {
    asm volatile("cp.async.bulk.shared::cluster.global.mbarrier::complete_tx::bytes [%0], [%1], %2, [%3];" :: "r"(dst), "l"(src), "r"(bytes), "r"(bar) : "memory");
}
__device__ __forceinline__ uint64_t pol_stream() { uint64_t p; asm volatile("createpolicy.fractional.L2::evict_first.b64 %0, 1.0;" : "=l"(p)); return p; }
__device__ __forceinline__ void bulk_g2s_s(uint32_t dst, const void* src, uint32_t bytes, uint32_t bar, uint64_t pol) {
    asm volatile("cp.async.bulk.shared::cluster.global.mbarrier::complete_tx::bytes.L2::cache_hint [%0], [%1], %2, [%3], %4;" :: "r"(dst), "l"(src), "r"(bytes), "r"(bar), "l"(pol) : "memory");
}
__device__ __forceinline__ void tma2d_s(uint32_t dst, const CUtensorMap* tm, int c0, int c1, uint32_t bar, uint64_t pol) {
    asm volatile("cp.async.bulk.tensor.2d.shared::cluster.global.mbarrier::complete_tx::bytes.L2::cache_hint [%0], [%1, {%3, %4}], [%2], %5;"
                 :: "r"(dst), "l"(tm), "r"(bar), "r"(c0), "r"(c1), "l"(pol) : "memory");
}
__device__ __forceinline__ void stsm4(uint32_t a, uint32_t r0, uint32_t r1, uint32_t r2, uint32_t r3) {
    asm volatile("stmatrix.sync.aligned.m8n8.x4.shared.b16 [%0], {%1,%2,%3,%4};" :: "r"(a), "r"(r0), "r"(r1), "r"(r2), "r"(r3) : "memory");
}
__device__ __forceinline__ void mma16816(float* c, uint32_t a0, uint32_t a1, uint32_t a2, uint32_t a3, uint32_t b0, uint32_t b1) {
    asm volatile("mma.sync.aligned.m16n8k16.row.col.f32.bf16.bf16.f32 {%0,%1,%2,%3}, {%4,%5,%6,%7}, {%8,%9}, {%0,%1,%2,%3};"
                 : "+f"(c[0]), "+f"(c[1]), "+f"(c[2]), "+f"(c[3]) : "r"(a0), "r"(a1), "r"(a2), "r"(a3), "r"(b0), "r"(b1));
}
__device__ __forceinline__ void mma1688(float* c, uint32_t a0, uint32_t a1, uint32_t b0) {
    asm volatile("mma.sync.aligned.m16n8k8.row.col.f32.bf16.bf16.f32 {%0,%1,%2,%3}, {%4,%5}, {%6}, {%0,%1,%2,%3};"
                 : "+f"(c[0]), "+f"(c[1]), "+f"(c[2]), "+f"(c[3]) : "r"(a0), "r"(a1), "r"(b0));
}
__device__ __forceinline__ uint32_t pack_bf16(float lo, float hi) {
    uint32_t r; asm("cvt.rn.bf16x2.f32 %0, %1, %2;" : "=r"(r) : "f"(hi), "f"(lo)); return r;
}
__device__ __forceinline__ uint32_t nz(uint32_t w) { return w == 0u ? 0x80000000u : w; }
__device__ __forceinline__ void sts32(uint32_t a, uint32_t v) { asm volatile("st.shared.u32 [%0], %1;" :: "r"(a), "r"(v) : "memory"); }
__device__ __forceinline__ void sts64f(uint32_t a, float x, float y) { asm volatile("st.shared.v2.f32 [%0], {%1,%2};" :: "r"(a), "f"(x), "f"(y) : "memory"); }
__device__ __forceinline__ void sts128(uint32_t a, uint4 v) {
    asm volatile("st.shared.v4.u32 [%0], {%1,%2,%3,%4};" :: "r"(a), "r"(v.x), "r"(v.y), "r"(v.z), "r"(v.w) : "memory");
}
__device__ __forceinline__ float4 lds128f(uint32_t a) {
    float4 v; asm volatile("ld.shared.v4.f32 {%0,%1,%2,%3}, [%4];" : "=f"(v.x), "=f"(v.y), "=f"(v.z), "=f"(v.w) : "r"(a) : "memory"); return v;
}
__device__ __forceinline__ float2 lds64f(uint32_t a) {
    float2 v; asm volatile("ld.shared.v2.f32 {%0,%1}, [%2];" : "=f"(v.x), "=f"(v.y) : "r"(a) : "memory"); return v;
}
__device__ __forceinline__ void st_async4(uint32_t a, uint32_t x, uint32_t y, uint32_t z, uint32_t w, uint32_t bar) {
    asm volatile("st.async.weak.shared::cluster.mbarrier::complete_tx::bytes.v4.b32 [%0], {%1,%2,%3,%4}, [%5];"
                 :: "r"(a), "r"(x), "r"(y), "r"(z), "r"(w), "r"(bar) : "memory");
}
__device__ __forceinline__ void st_async2(uint32_t a, uint32_t x, uint32_t y, uint32_t bar) {
    asm volatile("st.async.weak.shared::cluster.mbarrier::complete_tx::bytes.v2.b32 [%0], {%1,%2}, [%3];" :: "r"(a), "r"(x), "r"(y), "r"(bar) : "memory");
}
__device__ __forceinline__ void st_async1(uint32_t a, uint32_t x, uint32_t bar) {
    asm volatile("st.async.weak.shared::cluster.mbarrier::complete_tx::bytes.b32 [%0], %1, [%2];" :: "r"(a), "r"(x), "r"(bar) : "memory");
}
__device__ __forceinline__ void sts64(uint32_t a, uint32_t x, uint32_t y) { asm volatile("st.shared.v2.u32 [%0], {%1,%2};" :: "r"(a), "r"(x), "r"(y) : "memory"); }
__device__ __forceinline__ uint4 ld_relaxed4(const void* p) {
    uint4 v; asm volatile("ld.relaxed.gpu.global.v4.u32 {%0,%1,%2,%3}, [%4];" : "=r"(v.x), "=r"(v.y), "=r"(v.z), "=r"(v.w) : "l"(p) : "memory"); return v;
}
__device__ __forceinline__ uint32_t ld_relaxed1(const void* p) {
    uint32_t v; asm volatile("ld.relaxed.gpu.global.u32 %0, [%1];" : "=r"(v) : "l"(p) : "memory"); return v;
}
__device__ __forceinline__ void st_relaxed4(void* p, uint4 v) {
    asm volatile("st.relaxed.gpu.global.v4.u32 [%0], {%1,%2,%3,%4};" :: "l"(p), "r"(v.x), "r"(v.y), "r"(v.z), "r"(v.w) : "memory");
}
__device__ __forceinline__ void st_relaxed1(void* p, uint32_t v) {
    asm volatile("st.relaxed.gpu.global.u32 [%0], %1;" :: "l"(p), "r"(v) : "memory");
}
template <int LUT> __device__ __forceinline__ uint32_t lop3(uint32_t a, uint32_t b, uint32_t c) {
    uint32_t r; asm("lop3.b32 %0, %1, %2, %3, %4;" : "=r"(r) : "r"(a), "r"(b), "r"(c), "n"(LUT)); return r;
}
__device__ __forceinline__ void st_relaxed1_split(uint32_t lo, uint32_t hi, uint32_t v) {
    asm volatile("{ .reg .b64 a; mov.b64 a, {%0, %1}; st.relaxed.gpu.global.u32 [a], %2; }" :: "r"(lo), "r"(hi), "r"(v) : "memory");
}
__device__ __forceinline__ bool allnz(const uint4& v) { return min(min(v.x, v.y), min(v.z, v.w)) != 0u; }
__device__ __forceinline__ float ex2(float x) { float r; asm("ex2.approx.ftz.f32 %0, %1;" : "=f"(r) : "f"(x)); return r; }
#define WG_ROT 0
__device__ __forceinline__ int vtid() { return ((int)threadIdx.x + WG_ROT * 128) % 384; }
__device__ __forceinline__ int tid_pinned() { return __shfl_sync(0xffffffffu, vtid(), threadIdx.x & 31); }
__device__ __forceinline__ int opaque(int x) { int t; asm volatile("mov.u32 %0, %1;" : "=r"(t) : "r"(x)); return t; }
__device__ __forceinline__ const uint4* opaque_ptr(const uint4* p) { const uint4* r; asm volatile("mov.b64 %0, %1;" : "=l"(r) : "l"(p)); return r; }
__device__ __forceinline__ unsigned clk_dep(uint32_t dep) {
    unsigned t; asm volatile("{ .reg .pred p; .reg .u32 x; min.u32 x, %1, 7; setp.le.u32 p, x, 7; mov.u32 %0, 0; @p mov.u32 %0, %%clock; }" : "=r"(t) : "r"(dep) : "memory"); return t;
}
__device__ __forceinline__ unsigned gt32() { unsigned t; asm volatile("mov.u32 %0, %%globaltimer_lo;" : "=r"(t) :: "memory"); return t; }
__device__ __forceinline__ unsigned clk32() { unsigned t; asm volatile("mov.u32 %0, %%clock;" : "=r"(t) :: "memory"); return t; }

__device__ __forceinline__ void wg_fence() { asm volatile("wgmma.fence.sync.aligned;" ::: "memory"); }
__device__ __forceinline__ void wg_commit() { asm volatile("wgmma.commit_group.sync.aligned;" ::: "memory"); }
template <int N> __device__ __forceinline__ void wg_wait() { asm volatile("wgmma.wait_group.sync.aligned %0;" :: "n"(N) : "memory"); }
__host__ __device__ constexpr uint64_t make_desc(uint32_t addr, uint32_t lbo, uint32_t sbo, uint32_t swz) {
    return (uint64_t)((addr & 0x3FFFF) >> 4) | ((uint64_t)(lbo >> 4) << 16) | ((uint64_t)(sbo >> 4) << 32) | ((uint64_t)swz << 62);
}
#define ACC16(d) "+f"(d[0]), "+f"(d[1]), "+f"(d[2]), "+f"(d[3]), "+f"(d[4]), "+f"(d[5]), "+f"(d[6]), "+f"(d[7]), \
                 "+f"(d[8]), "+f"(d[9]), "+f"(d[10]), "+f"(d[11]), "+f"(d[12]), "+f"(d[13]), "+f"(d[14]), "+f"(d[15])
__device__ __forceinline__ void wgmma_rs_n32(float* d, const uint32_t* a, uint64_t db, int acc) {
    asm volatile("{\n.reg .pred p;\nsetp.ne.b32 p, %21, 0;\n"
                 "wgmma.mma_async.sync.aligned.m64n32k16.f32.bf16.bf16 {%0,%1,%2,%3,%4,%5,%6,%7,%8,%9,%10,%11,%12,%13,%14,%15}, {%16,%17,%18,%19}, %20, p, 1, 1, 0;\n}"
                 : ACC16(d) : "r"(a[0]), "r"(a[1]), "r"(a[2]), "r"(a[3]), "l"(db), "r"(acc));
}
#define OUT16(d) "=f"(d[0]), "=f"(d[1]), "=f"(d[2]), "=f"(d[3]), "=f"(d[4]), "=f"(d[5]), "=f"(d[6]), "=f"(d[7]), \
                 "=f"(d[8]), "=f"(d[9]), "=f"(d[10]), "=f"(d[11]), "=f"(d[12]), "=f"(d[13]), "=f"(d[14]), "=f"(d[15])
__device__ __forceinline__ void wgmma_rs_n32_first(float* d, const uint32_t* a, uint64_t db) {
    asm volatile("wgmma.mma_async.sync.aligned.m64n32k16.f32.bf16.bf16 {%0,%1,%2,%3,%4,%5,%6,%7,%8,%9,%10,%11,%12,%13,%14,%15}, {%16,%17,%18,%19}, %20, 0, 1, 1, 0;"
                 : OUT16(d) : "r"(a[0]), "r"(a[1]), "r"(a[2]), "r"(a[3]), "l"(db));
}
__device__ __forceinline__ void wgmma_ss_n32_ta(float* d, uint64_t da, uint64_t db, int acc) {
    asm volatile("{\n.reg .pred p;\nsetp.ne.b32 p, %18, 0;\n"
                 "wgmma.mma_async.sync.aligned.m64n32k16.f32.bf16.bf16 {%0,%1,%2,%3,%4,%5,%6,%7,%8,%9,%10,%11,%12,%13,%14,%15}, %16, %17, p, 1, 1, 1, 0;\n}"
                 : ACC16(d) : "l"(da), "l"(db), "r"(acc));
}
__device__ __forceinline__ void wgmma_ss_n32_ta_first(float* d, uint64_t da, uint64_t db) {
    asm volatile("wgmma.mma_async.sync.aligned.m64n32k16.f32.bf16.bf16 {%0,%1,%2,%3,%4,%5,%6,%7,%8,%9,%10,%11,%12,%13,%14,%15}, %16, %17, 0, 1, 1, 1, 0;"
                 : OUT16(d) : "l"(da), "l"(db));
}
__device__ __forceinline__ void wgmma_ss_n8_tatb(float* d, uint64_t da, uint64_t db, int acc) {
    asm volatile("{\n.reg .pred p;\nsetp.ne.b32 p, %6, 0;\n"
                 "wgmma.mma_async.sync.aligned.m64n8k16.f32.bf16.bf16 {%0,%1,%2,%3}, %4, %5, p, 1, 1, 1, 1;\n}"
                 : "+f"(d[0]), "+f"(d[1]), "+f"(d[2]), "+f"(d[3]) : "l"(da), "l"(db), "r"(acc));
}

__device__ __forceinline__ void wgmma_ss_n40_tatb(float* d, uint64_t da, uint64_t db, int acc) {
    asm volatile("{\n.reg .pred p;\nsetp.ne.b32 p, %22, 0;\n"
                 "wgmma.mma_async.sync.aligned.m64n40k16.f32.bf16.bf16 {%0,%1,%2,%3,%4,%5,%6,%7,%8,%9,%10,%11,%12,%13,%14,%15,%16,%17,%18,%19}, %20, %21, p, 1, 1, 1, 1;\n}"
                 : ACC16(d), "+f"(d[16]), "+f"(d[17]), "+f"(d[18]), "+f"(d[19]) : "l"(da), "l"(db), "r"(acc));
}
__device__ __forceinline__ void wgmma_rs_n32x(float* d, uint32_t a0, uint32_t a1, uint32_t a2, uint32_t a3, uint64_t db, int acc) {
    const uint32_t a[4] = {a0, a1, a2, a3};
    wgmma_rs_n32(d, a, db, acc);
}
__device__ __forceinline__ float rcp(float x) { float r; asm("rcp.approx.ftz.f32 %0, %1;" : "=f"(r) : "f"(x)); return r; }
__device__ __forceinline__ uint4 lds128(uint32_t a) {
    uint4 v; asm volatile("ld.shared.v4.u32 {%0,%1,%2,%3}, [%4];" : "=r"(v.x), "=r"(v.y), "=r"(v.z), "=r"(v.w) : "r"(a) : "memory"); return v;
}
__device__ __forceinline__ uint2 lds64(uint32_t a) { uint2 v; asm volatile("ld.shared.v2.u32 {%0,%1}, [%2];" : "=r"(v.x), "=r"(v.y) : "r"(a) : "memory"); return v; }
__device__ __forceinline__ uint32_t lds32(uint32_t a) { uint32_t v; asm volatile("ld.shared.u32 %0, [%1];" : "=r"(v) : "r"(a) : "memory"); return v; }
__device__ __forceinline__ uint32_t hadd2(uint32_t a, uint32_t b) { uint32_t r; asm("add.rn.bf16x2 %0, %1, %2;" : "=r"(r) : "r"(a), "r"(b)); return r; }
__device__ __forceinline__ uint32_t hmax2(uint32_t a, uint32_t b) { uint32_t r; asm("max.bf16x2 %0, %1, %2;" : "=r"(r) : "r"(a), "r"(b)); return r; }
__device__ __forceinline__ float bf_lo(uint32_t w) { return __uint_as_float(w << 16); }
__device__ __forceinline__ float bf_hi(uint32_t w) { return __uint_as_float(w & 0xffff0000u); }

constexpr uint32_t SB0 = 1024;
constexpr uint32_t SM_WQ = 0;
constexpr uint32_t SM_WO = 81920;
constexpr uint32_t SM_XR = 163840;
constexpr uint32_t SM_MEM = SM_XR + 10 * 4096;
constexpr uint32_t SM_KB = SM_MEM + 10240;
constexpr uint32_t SM_VB = SM_KB + 5120;
constexpr uint32_t SM_SC = SM_VB + 5120;
constexpr uint32_t SM_XIN = SM_SC + 5120;
constexpr uint32_t SM_BAR = SM_SC + 512;
constexpr uint32_t SM_IB = SM_SC + 640 + 512;
constexpr uint32_t REC_SMEM = SM_XIN + 2048;
constexpr uint32_t REC_SMEM_L = REC_SMEM;
static_assert(REC_SMEM_L <= 232448, "smem");
constexpr uint32_t MB_W0 = 0, MB_W1 = 8, MB_X = 24, MB_W2 = 32, MB_G = 40;
constexpr int NB_ALL = 1, NB_TS = 2, NB_QK = 3, NB_O = 5, NB_XR = 7, NB_TA = 8, NB_WG2 = 9, NB_PUB = 10;

constexpr float SCALE_A = 0.07216878364870322f * 1.4426950408889634f;
#define R_WG0 208
#define R_WG2 88
#define Q_PF 6
#define O_PF 2
#define EVX 1
#define POLL_P 130
#define QA_AT 9
#define QA_N 3
#define QB_AT 19
#define PAUSE 1
#define SECMAJ 1
#define RS_CH 3
#define AG_D 300
#define AG_E 0
#define RS_AT 1250
#define AG_AT 2050
#define X_AT 0
#define TS_AT 0

__device__ __forceinline__ char* rs_base() { return (char*)(((uintptr_t)g_rs_raw + (2 << 20) - 1) & ~(uintptr_t)((2 << 20) - 1)); }
__device__ __forceinline__ uint32_t hashbit(uint32_t a) { return ((a >> 12) ^ (a >> 13) ^ (a >> 16) ^ (a >> 17) ^ (a >> 19)) & 1u; }
__device__ __forceinline__ uint32_t rs_off(int r, uint32_t side) {
    const uint32_t a = r * 8192;
    return a + ((side ^ hashbit(a)) << 12);
}
constexpr uint32_t AG_BASE = NRED * 8192;
__device__ __forceinline__ uint32_t ag_off(int b, uint32_t side) {
    const uint32_t a = AG_BASE + b * 8192;
    return a + ((side ^ hashbit(a)) << 12);
}
__device__ __forceinline__ uint32_t get_side(int cta) {
    uint32_t v; int n = 0;
#pragma unroll 1
    do { asm volatile("ld.relaxed.gpu.global.u32 %0, [%1];" : "=r"(v) : "l"(&g_side[cta * 8]) : "memory"); } while (v == 0u && ++n < SPIN_MAX);
    return v & 1u;
}
__device__ __forceinline__ void spin_until(unsigned t0, unsigned d) {
    asm volatile("{\n.reg .pred p;\n.reg .u32 t, h;\n.reg .u64 c;\nSU_L_%=:\nmov.u64 c, %%clock64;\nmov.b64 {t, h}, c;\nsub.u32 t, t, %0;\nand.b32 h, h, 0x80000000;\nor.b32 t, t, h;\nsetp.lt.u32 p, t, %1;\n@p bra.uni SU_L_%=;\n}"
                 :: "r"(t0), "r"(d) : "memory");
}
__device__ __forceinline__ void cpa16(uint32_t dst, const void* src) {
    asm volatile("cp.async.cg.shared.global [%0], [%1], 16;" :: "r"(dst), "l"(src) : "memory");
}
__device__ __forceinline__ void cpa_wait() { asm volatile("cp.async.wait_all;" ::: "memory"); }
__device__ __forceinline__ void cpa_commit() { asm volatile("cp.async.commit_group;" ::: "memory"); }
__device__ __forceinline__ void cpa_wait2() { asm volatile("cp.async.wait_group 2;" ::: "memory"); }

__device__ __forceinline__ void issue_x(uint32_t sb, const CUtensorMap* tm_x, int seg, int g) {
    mbar_expect(sb + SM_BAR + MB_G + 8 * g, 20480);
    asm volatile("cp.async.bulk.tensor.3d.shared::cluster.global.mbarrier::complete_tx::bytes [%0], [%1, {0, %3, %4}], [%2];"
                 :: "r"(sb + SM_XR + g * 20480), "l"(tm_x), "r"(sb + SM_BAR + MB_G + 8 * g), "r"(seg * 32), "r"(5 * g) : "memory");
}
__device__ __forceinline__ uint64_t mk64(uint32_t lo, uint32_t hi) { uint64_t r; asm("mov.b64 %0, {%1, %2};" : "=l"(r) : "r"(lo), "r"(hi)); return r; }
template <int OFF> __device__ __forceinline__ void st_relaxed1_a(uint64_t a, uint32_t v) {
    asm volatile("st.relaxed.gpu.global.u32 [%0 + %2], %1;" :: "l"(a), "r"(v), "n"(OFF) : "memory");
}
#define PIN1(a) asm volatile("" :: "r"(a));
#define PIN2(a, b) asm volatile("" :: "r"(a), "r"(b));
#define PINL(a) asm volatile("" :: "l"(a));
#define PINF(a) asm volatile("" :: "f"((a)[0]), "f"((a)[1]), "f"((a)[2]), "f"((a)[3]));
template <int OFF> __device__ __forceinline__ void st_relaxed1_off(uint32_t lo, uint32_t hi, uint32_t v) {
    asm volatile("{ .reg .b64 a; mov.b64 a, {%0, %1}; st.relaxed.gpu.global.u32 [a + %3], %2; }" :: "r"(lo), "r"(hi), "r"(v), "n"(OFF) : "memory");
}
template <int OFF> __device__ __forceinline__ uint32_t ld_relaxed1_off(const void* p) {
    uint32_t v; asm volatile("ld.relaxed.gpu.global.u32 %0, [%1 + %2];" : "=r"(v) : "l"(p), "n"(OFF) : "memory"); return v;
}

constexpr uint64_t DESC_X = make_desc(SB0 + SM_XR, 16, 1024, 1);
#define XOFF(k) ((((k) / 4) * 4096 + ((k) % 4) * 32) >> 4)

#define SCHED_FENCE asm volatile("{\n.reg .pred p;\nsetp.eq.u32 p, %0, 0;\n@p exit;\n}" :: "r"(sb) : "memory");
#define LD_T(buf, a) { ldsm4t((buf)[0], (buf)[1], (buf)[2], (buf)[3], a); }
#define LD_Q(i) LD_T(Q[i], ta + SM_WQ + (20 * G + (i)) * 2048)
template <int G, bool FIRST>
__device__ __forceinline__ void token_gemm(uint32_t sb, const uint32_t (&W)[160], uint32_t (&Q)[Q_PF][4], uint32_t ta, int seg, int tx, int wu) {
    const int lane = tx & 31;
    float a[16];
    wg_fence();
#pragma unroll
    for (int k = 0; k < 20; k++) {
        if (k == 0) wgmma_rs_n32_first(a, W, DESC_X + XOFF(20 * G)); else wgmma_rs_n32(a, &W[k * 4], DESC_X + XOFF(20 * G + k), 1);
        if (!FIRST && k == QA_AT) {
            __syncwarp();
#pragma unroll
            for (int i = 0; i < QA_N; i++) LD_Q(i)
            __syncwarp();
        }
    }
    wg_commit();
    const uint32_t off = sb + wu * 1280 + (((lane >> 3) & 1) * 5 + (lane >> 4)) * 128 + (lane & 7) * 16;
    const uint32_t b1 = off + (G == 0 ? SM_KB : SM_VB), b2 = off + (G == 0 ? SM_VB : SM_KB);
    wg_wait<0>();
    uint32_t u[8];
#pragma unroll
    for (int i = 0; i < 8; i++) u[i] = pack_bf16(a[2 * i], a[2 * i + 1]);
    if (!FIRST && PAUSE) bar_sync(NB_PUB, 384);
    stsm4(b1, u[0], u[1], u[2], u[3]); stsm4(b1 + 256, u[4], u[5], u[6], u[7]);
    bar_sync(NB_TA, 256);
    wg_fence();
#pragma unroll
    for (int k = 0; k < 20; k++) {
        if (k == 0) wgmma_rs_n32_first(a, &W[80], DESC_X + XOFF(20 * G)); else wgmma_rs_n32(a, &W[80 + k * 4], DESC_X + XOFF(20 * G + k), 1);
        if (k == QB_AT) {
            __syncwarp();
            ldsm4(u[0], u[1], u[2], u[3], b2); ldsm4(u[4], u[5], u[6], u[7], b2 + 256);
            if (!FIRST) {
#pragma unroll
                for (int i = QA_N; i < 4; i++) LD_Q(i)
            }
            __syncwarp();
        }
    }
    wg_commit();
    wg_wait<0>();
    SCHED_FENCE
#pragma unroll
    for (int i = 0; i < 8; i++) u[i] = pack_bf16(a[2 * i] + bf_lo(u[i]), a[2 * i + 1] + bf_hi(u[i]));
    stsm4(b2, u[0], u[1], u[2], u[3]); stsm4(b2 + 256, u[4], u[5], u[6], u[7]);
    if (FIRST) mbar_wait(sb + SM_BAR + MB_W1, 0);
#pragma unroll
    for (int i = FIRST ? 0 : 4; i < Q_PF; i++) LD_Q(i)
}
#undef LD_Q

#define LD_O(buf, a) { _Pragma("unroll") for (int ks = 0; ks < 4; ks++) ldsm4t((buf)[4 * ks], (buf)[4 * ks + 1], (buf)[4 * ks + 2], (buf)[4 * ks + 3], (a) + ks * 2048); }
#define MMA_K(c, P, ks) mma16816(c, P[4 * (ks)], P[4 * (ks) + 1], P[4 * (ks) + 2], P[4 * (ks) + 3], B[2 * (ks)], B[2 * (ks) + 1]);
#define MMA_O(c, P) { MMA_K(c, P, 0) MMA_K(c, P, 1) MMA_K(c, P, 2) MMA_K(c, P, 3) }
__host__ __device__ constexpr int qload(int j) {
    int n = 0;
    for (int k = 0; k < 20; k++) {
        if (!(k & 1)) { if (n == j) return k >> 1; n++; }
        if (k >= Q_PF) { if (n == j) return 10 + k; n++; }
    }
    return -1;
}

template <int G>
__device__ __forceinline__ void rec_weights(uint32_t sb, uint32_t rank, const CUtensorMap* tm_x, const CUtensorMap* tm_wq,
                                            const CUtensorMap* tm_wo, int head) {
    const int tx0 = tid_pinned();
    const int wu = __shfl_sync(0xffffffffu, (int)(threadIdx.x >> 5) & 3, 0);
    uint32_t W[160];
    mbar_wait(sb + SM_BAR + MB_W0, 0);
    {
        const int lane = tx0 & 31;
        const uint32_t d = ((lane >> 4) & 1) * 8 + (lane & 7), ch = 2 * wu + ((lane >> 3) & 1);
        const uint32_t a = sb + d * 128 + ((ch ^ (d & 7)) << 4) + G * 20 * 2048;
#pragma unroll
        for (int k = 0; k < 20; k++) LD_T(&W[4 * k], a + (G == 0 ? SM_WO : SM_WQ) + k * 2048)
#pragma unroll
        for (int k = 0; k < 20; k++) LD_T(&W[80 + 4 * k], a + (G == 0 ? SM_WQ : SM_WO) + k * 2048)
    }
    bar_sync(NB_TA, 256);
    if (G == 0 && tx0 == 0) {
        mbar_expect(sb + SM_BAR + MB_W1, 81920);
        mbar_expect(sb + SM_BAR + MB_W2, 81920);
        for (int i = 0; i < 5; i++) tma2d(sb + SM_WQ + i * 16384, tm_wq, head * DH + rank * 64, i * 128, sb + SM_BAR + MB_W1);
        for (int i = 0; i < 10; i++) tma2d(sb + SM_WO + i * 8192, tm_wo, i * 64, head * DH + rank * 64, sb + SM_BAR + MB_W2);
    }
    __syncwarp();
    asm volatile("barrier.cluster.wait.acquire;" ::: "memory");
    mbar_wait(sb + SM_BAR + MB_G + 8 * G, 0);
    const uint32_t ta = sb + (((tx0 >> 4) & 1) * 8 + (tx0 & 7)) * 128 + (((2 * wu + ((tx0 >> 3) & 1)) ^ (tx0 & 7)) << 4);
    uint32_t QP[Q_PF][4];
    token_gemm<G, true>(sb, W, QP, ta, 0, opaque(tx0), wu);
    const uint32_t dest = (rank + 1 + G) % 3;
    for (int s = 0; s < NSEG; s++) {
        {
            const uint32_t mb = sb + (opaque(tx0) & 31) * 16 + SM_MEM + G * 5120;
            uint32_t Q[20][4], b[10][4];
#pragma unroll
            for (int i = 0; i < Q_PF; i++) { Q[i][0] = QP[i][0]; Q[i][1] = QP[i][1]; Q[i][2] = QP[i][2]; Q[i][3] = QP[i][3]; }
            PIN1(mb)
            SCHED_FENCE
            bar_sync(NB_ALL, 384);
            float cq[4] = {0.f, 0.f, 0.f, 0.f}, ck[4] = {0.f, 0.f, 0.f, 0.f}, cv[4] = {0.f, 0.f, 0.f, 0.f};
#define QLD(j) { constexpr int x_ = qload(j); if (x_ >= 10) LD_T(Q[x_ >= 10 ? x_ - 10 : 0], ta + SM_WQ + (20 * G + x_ - 10) * 2048) else if (x_ >= 0) LD_T(b[x_ >= 0 && x_ < 10 ? x_ : 0], mb + x_ * 512) }
#define QSTEP(k) { \
                mma16816(cq, Q[k][0], Q[k][1], Q[k][2], Q[k][3], b[(k) >> 1][2 * ((k) & 1)], b[(k) >> 1][2 * ((k) & 1) + 1]); \
                if ((k) > 0) QLD(Q_NI - 1 + (k) + ((k) >> 1)) \
                SCHED_FENCE \
                mma16816(ck, W[80 * G + 4 * (k)], W[80 * G + 4 * (k) + 1], W[80 * G + 4 * (k) + 2], W[80 * G + 4 * (k) + 3], b[(k) >> 1][2 * ((k) & 1)], b[(k) >> 1][2 * ((k) & 1) + 1]); \
                mma16816(cv, W[80 - 80 * G + 4 * (k)], W[80 - 80 * G + 4 * (k) + 1], W[80 - 80 * G + 4 * (k) + 2], W[80 - 80 * G + 4 * (k) + 3], b[(k) >> 1][2 * ((k) & 1)], b[(k) >> 1][2 * ((k) & 1) + 1]); \
                if ((k) & 1) QLD(Q_NI + (k) + ((k) >> 1)) \
                SCHED_FENCE }
            constexpr int Q_NI = 8 - Q_PF;
            QLD(0) if (Q_NI > 1) QLD(1) if (Q_NI > 2) QLD(2)
            SCHED_FENCE
            QSTEP(0) QSTEP(1) QSTEP(2) QSTEP(3) QSTEP(4) QSTEP(5) QSTEP(6) QSTEP(7) QSTEP(8) QSTEP(9)
            QSTEP(10) QSTEP(11) QSTEP(12) QSTEP(13) QSTEP(14) QSTEP(15) QSTEP(16) QSTEP(17)
            const uint32_t a = sb + (opaque(tx0) & 31) * 4 + wu * 1280;
            QSTEP(18) QSTEP(19)
#undef QSTEP
#undef QLD
            constexpr uint32_t ok = G == 0 ? SM_KB + 512 : SM_SC + 256, ov = G == 0 ? SM_VB + 512 : SM_SC + 384;
            sts32(a + SM_SC + G * 128, pack_bf16(cq[0], cq[1])); sts32(a + SM_SC + G * 128 + 640, pack_bf16(cq[2], cq[3]));
            sts32(a + ok, pack_bf16(ck[0], ck[1])); sts32(a + ok + 640, pack_bf16(ck[2], ck[3]));
            sts32(a + ov, pack_bf16(cv[0], cv[1])); sts32(a + ov + 640, pack_bf16(cv[2], cv[3]));
        }
        bar_arrive(NB_XR, 384);
        unsigned t_o = 0;
        {
            const int tx = opaque(tx0);
            const uint32_t oa = ta + SM_WO + 3 * 8192 * dest;
            uint32_t A[16], A2[16], A3[16];
            if (s == 0) mbar_wait(sb + SM_BAR + MB_W2, 0);
            bar_sync(NB_QK, 384);
            {
                const uint32_t a = sb + (tx & 31) * 4 + wu * 1280;
                constexpr uint32_t of = (G == 0 ? SM_VB : SM_KB) + 512, op = SM_SC + 384 - G * 128;
                const uint32_t y0 = lds32(a + of), y1 = lds32(a + op), y2 = lds32(a + of + 640), y3 = lds32(a + op + 640);
                SCHED_FENCE
                LD_O(A, oa)
                SCHED_FENCE
                sts32(a + of, hadd2(y0, y1)); sts32(a + of + 640, hadd2(y2, y3));
                fence_async_smem();
                __syncwarp();
                if (elect_one()) {
                    asm volatile("cp.async.bulk.global.shared::cta.bulk_group.L2::cache_hint [%0], [%1], %2, %3;"
                                 :: "l"(g_kv + (size_t)(s * NCTA + blockIdx.x) * 10240 + (1 - G) * 5120 + wu * 1280), "r"(sb + SM_KB + (1 - G) * 5120 + wu * 1280), "r"(1280), "l"(pol_stream()) : "memory");
                    asm volatile("cp.async.bulk.commit_group;" ::: "memory");
                }
                __syncwarp();
            }
            LD_O(A2, oa + 8192)
            if (s == NSEG - 1) {
                asm volatile("cp.async.bulk.wait_group 0;" ::: "memory");
                bar_sync(NB_TA, 256);
                if (G == 0 && tx0 == 0) asm volatile("red.relaxed.gpu.global.add.u32 [%0], 1;" :: "l"(&g_ctl.seg[31]) : "memory");
                break;
            }
            const uint32_t dd = (dest - rank) << 24;
            const uint32_t ib = sb + dd + SM_IB + wu * 8, id = sb + dd + SM_MEM + G * 4096 + wu * 256 + (tx & 31) * 8;
            const uint32_t qq = sb + SM_SC + ((tx >> 3) & 3) * 640 + (tx & 7) * 16;
            PIN2(qq, id)
            SCHED_FENCE
            bar_sync(NB_O, 384);
            if (TS_AT) t_o = clk32();
            uint32_t B[8];
            ldsm4t(B[0], B[1], B[2], B[3], qq);
            SCHED_FENCE
            ldsm4t(B[4], B[5], B[6], B[7], qq + 2560);
            SCHED_FENCE
            float c[4] = {0.f, 0.f, 0.f, 0.f}, c2[4] = {0.f, 0.f, 0.f, 0.f}, c3[4] = {0.f, 0.f, 0.f, 0.f}, c4[4] = {0.f, 0.f, 0.f, 0.f};
            MMA_K(c, A, 0) MMA_K(c2, A, 1) MMA_K(c3, A2, 0)
            SCHED_FENCE
            MMA_K(c, A, 2) MMA_K(c2, A, 3) MMA_K(c3, A2, 1)
            LD_T(&A3[0], oa + 2 * 8192) LD_T(&A3[4], oa + 2 * 8192 + 2048) LD_T(&A3[8], oa + 2 * 8192 + 2 * 2048)
            SCHED_FENCE
            MMA_K(c3, A2, 2)
            st_async2(id + 1024, pack_bf16(c[0] + c2[0], c[1] + c2[1]), pack_bf16(c[2] + c2[2], c[3] + c2[3]), ib);
            LD_T(&A3[12], oa + 2 * 8192 + 3 * 2048)
            SCHED_FENCE
            MMA_K(c3, A2, 3)
            st_async2(id + 2048, pack_bf16(c3[0], c3[1]), pack_bf16(c3[2], c3[3]), ib);
            SCHED_FENCE
            float c5[4] = {0.f, 0.f, 0.f, 0.f};
            MMA_K(c4, A3, 0) MMA_K(c5, A3, 1) MMA_K(c4, A3, 2) MMA_K(c5, A3, 3)
            st_async2(id + 3072, pack_bf16(c4[0] + c5[0], c4[1] + c5[1]), pack_bf16(c4[2] + c5[2], c4[3] + c5[3]), ib + 32);
            SCHED_FENCE
            asm volatile("cp.async.bulk.wait_group 0;" ::: "memory");
            mbar_wait(sb + SM_BAR + MB_G + 8 * G, (s + 1) & 1);
            bar_sync(NB_TS, 384);
        }
        if (TS_AT) spin_until(t_o, TS_AT);
        token_gemm<G, false>(sb, W, QP, ta, s + 1, opaque(tx0), wu);
    }
}

#define AG_WEAK 0
#define AG_OP "ld.relaxed.gpu.global.v4.u32"
__device__ __forceinline__ uint4 AG_LD(const void* p) {
    uint4 v; asm volatile(AG_OP " {%0,%1,%2,%3}, [%4];" : "=r"(v.x), "=r"(v.y), "=r"(v.z), "=r"(v.w) : "l"(p) : "memory"); return v;
}
__device__ __forceinline__ void ag_ld_if(uint4& v, const void* p, bool c) {
    asm volatile("{\n.reg .pred p;\nsetp.ne.u32 p, %5, 0;\n@p " AG_OP " {%0,%1,%2,%3}, [%4];\n}" : "+r"(v.x), "+r"(v.y), "+r"(v.z), "+r"(v.w) : "l"(p), "r"((uint32_t)c) : "memory");
}
__device__ __forceinline__ void sts128_if(uint32_t a, uint4 v, bool c) {
    asm volatile("{\n.reg .pred p;\nsetp.ne.u32 p, %5, 0;\n@p st.shared.v4.u32 [%0], {%1,%2,%3,%4};\n}" :: "r"(a), "r"(v.x), "r"(v.y), "r"(v.z), "r"(v.w), "r"((uint32_t)c) : "memory");
}
__device__ __forceinline__ bool rs_try(const uint32_t (&L)[8], uint32_t ntag, uint32_t keep, uint64_t pub, uint32_t idle) {
    const float lo = ((bf_lo(L[0]) + bf_lo(L[1])) + (bf_lo(L[2]) + bf_lo(L[3]))) + ((bf_lo(L[4]) + bf_lo(L[5])) + (bf_lo(L[6]) + bf_lo(L[7])));
    const float hi = ((bf_hi(L[0]) + bf_hi(L[1])) + (bf_hi(L[2]) + bf_hi(L[3]))) + ((bf_hi(L[4]) + bf_hi(L[5])) + (bf_hi(L[6]) + bf_hi(L[7])));
    const float l1 = __shfl_xor_sync(0xffffffffu, lo, 8), h1 = __shfl_xor_sync(0xffffffffu, hi, 8), l2 = __shfl_xor_sync(0xffffffffu, lo, 16);
    const float h2 = __shfl_xor_sync(0xffffffffu, hi, 16), l3 = __shfl_xor_sync(0xffffffffu, lo, 24), h3 = __shfl_xor_sync(0xffffffffu, hi, 24);
    const uint32_t bad = lop3<0xA8>(lop3<0xFE>(lop3<0x7E>(L[0], L[1], ntag), lop3<0x7E>(L[2], L[3], ntag), lop3<0x7E>(L[4], L[5], ntag)), lop3<0x7E>(L[6], L[7], ntag), 1u);
    const bool ok = __all_sync(0xffffffffu, bad == 0u);
    const uint32_t w = lop3<0xE4>(ntag, pack_bf16((lo + l1) + (l2 + l3), (hi + h1) + (h2 + h3)), keep);
    asm volatile("{\n.reg .pred p, q;\nsetp.ne.u32 p, %0, 0;\nsetp.eq.and.u32 q, %3, 0, p;\n@q st.relaxed.gpu.global.u32 [%1], %2;\n}"
                 :: "r"((uint32_t)ok), "l"(pub), "r"(w), "r"(idle) : "memory");
    return ok;
}

__device__ __forceinline__ void rec_comm(uint32_t sb, uint32_t rank, const bf16* mem0, const CUtensorMap* tm_x, int head) {
    const uint32_t d1 = (rank == 2 ? -2 : 1) << 24, d2 = (rank == 0 ? 2 : -1) << 24;
    const int tid = tid_pinned() - 256, lane = tid & 31;
    const int v = __shfl_sync(0xffffffffu, (int)(threadIdx.x >> 5) & 3, 0);
    for (int c = tid; c < 640; c += 128) {
        uint32_t wd[4];
#pragma unroll
        for (int r = 0; r < 4; r++) {
            uint32_t lo = *(const unsigned short*)(mem0 + (2 * r) * DM + c), hi = *(const unsigned short*)(mem0 + (2 * r + 1) * DM + c);
            wd[r] = lo | (hi << 16);
        }
        sts128(sb + SM_MEM + c * 16, make_uint4(wd[0], wd[1], wd[2], wd[3]));
    }
    if (v == 3 && blockIdx.x < NRED) {
        char* p = rs_base() + ag_off(blockIdx.x >> 5, 0u) + (blockIdx.x & 31) * 128 + lane * 4;
        st_relaxed1(p, 0u); st_relaxed1((char*)((uintptr_t)p ^ 4096), 0u);
        asm volatile("fence.acq_rel.gpu;" ::: "memory");
    }
    __syncwarp();
    if (tid == 127) {
        unsigned best[2] = {~0u, ~0u};
        st_relaxed1(rs_base() + (2 << 20) - 8192 + blockIdx.x * 32, 0u);
        st_relaxed1(rs_base() + (2 << 20) - 4096 + blockIdx.x * 32, 0u);
        for (int rep = 0; rep < 4; rep++) {
#pragma unroll
            for (int hh = 0; hh < 2; hh++) {
                unsigned* p = (unsigned*)(rs_base() + (2 << 20) - 8192 + hh * 4096 + blockIdx.x * 32);
                unsigned dt;
                asm volatile("{ .reg .pred q; .reg .u32 o, a, b;\nmov.u32 a, %%clock;\natom.relaxed.gpu.global.add.u32 o, [%1], 2;\n"
                             "and.b32 o, o, 1;\nsetp.eq.u32 q, o, 0;\nmov.u32 b, 0;\n@q mov.u32 b, %%clock;\nsub.u32 %0, b, a; }"
                             : "=r"(dt) : "l"(p) : "memory");
                best[hh] = min(best[hh], dt);
            }
        }
        st_relaxed1(&g_side[blockIdx.x * 8], 2u | hashbit((2 << 20) - 8192 + (best[1] < best[0]) * 4096));
    }
    __syncwarp();
    asm volatile("barrier.cluster.wait.acquire;" ::: "memory");
    const uint32_t own0 = v < 2 ? 0u : v - 1u;
    uint32_t selm;
    {
        const int T = (lane >> 1) == 0 ? 36 + v : 12 * rank + 4 * ((lane >> 1) - 1) + v, r = 2 * T + (lane & 1);
        selm = __ballot_sync(0xffffffffu, lane < 8 && ((rs_off(r, get_side(lane < 8 ? r : 0)) >> 12) & 1u));
    }
    if (tid < NRED) get_side(tid);
    asm volatile("fence.acq_rel.gpu;" ::: "memory");
    if (tid < 2 && blockIdx.x < NSEG) asm volatile("cp.async.bulk.prefetch.tensor.3d.L2.global [%0, {0, %1, %2}];" :: "l"(tm_x), "r"(blockIdx.x * 32), "r"(tid * 5) : "memory");
    __syncwarp();
    const uint32_t myside = __shfl_sync(0xffffffffu, get_side(blockIdx.x), 0);
    const uint32_t glo0 = (uint32_t)(uintptr_t)rs_base(), ghi = (uint32_t)((uintptr_t)rs_base() >> 32);
    const uint32_t ro = glo0 + rs_off(blockIdx.x, myside), po = glo0 + ag_off(blockIdx.x >> 5, 0u) + (blockIdx.x & 31) * 128 + v * 32;
    const uint32_t ao0 = glo0 + ag_off(0, myside), ao1 = glo0 + ag_off(1, myside), ao2 = glo0 + ag_off(2, myside);
    const bool mine0 = own0 == rank;
    const int tid0 = tid;
    constexpr int rs_at = RS_AT, ag_at = AG_AT;
    const unsigned ag_d = AG_D + ((blockIdx.x < 72 && blockIdx.x % 24 >= 16) ? 0 : AG_E);
    int err = 0;
    uint32_t A[16];
    bar_sync(NB_ALL, 384);

    for (int s = 0; s < NSEG; s++) {
        const int tid = opaque(tid0), lane = tid & 31;
        const uint32_t par = (s & 1) + (tid >> 10);
        const unsigned t_s = clk32();
        const uint32_t t8 = sb + (lane & 7) * 16, qq = t8 + SM_SC + (lane >> 3) * 640;
        const uint32_t xb = sb + SM_BAR + MB_X;
        if (tid == 0 && s > 0) asm volatile("red.relaxed.gpu.global.add.u32 [%0], 1;" :: "l"(&g_ctl.seg[(s - 1) >> 1]) : "memory");
        const uint32_t glo = glo0 + v * 16384 + (lane >> 3) * 1024 + head * 32 + (lane & 7) * 4;
#define RS_AD(i, h) mk64(((i) == 0 ? glo : glo + rank * (24 * 8192)) + (((selm >> (2 * (i) + (h))) & 1u) << 12), ghi)
#define RS_OF(i, h) (((i) == 0 ? 72 : 8 * ((i) - 1)) * 8192 + (h) * 8192)
        if (s == NSEG - 1) {
            if (mine0) { st_relaxed1_a<RS_OF(0, 0)>(RS_AD(0, 0), 0u); st_relaxed1_a<RS_OF(0, 1)>(RS_AD(0, 1), 0u); }
            st_relaxed1_a<RS_OF(1, 0)>(RS_AD(1, 0), 0u); st_relaxed1_a<RS_OF(1, 1)>(RS_AD(1, 1), 0u); st_relaxed1_a<RS_OF(2, 0)>(RS_AD(2, 0), 0u);
            st_relaxed1_a<RS_OF(2, 1)>(RS_AD(2, 1), 0u); st_relaxed1_a<RS_OF(3, 0)>(RS_AD(3, 0), 0u); st_relaxed1_a<RS_OF(3, 1)>(RS_AD(3, 1), 0u);
            bar_sync(NB_XR, 384);
            bar_arrive(NB_QK, 384);
            break;
        }
        if (lane < 3 && (lane < 2 || v == 0)) mbar_expect(lane == 2 ? xb : sb + SM_IB + lane * 32 + v * 8, lane == 2 ? 1920u : lane == 1 ? 512u : mine0 ? 1536u : 1024u);
        __syncwarp();
        const uint32_t xi = sb + SM_XIN + lane * 16, l4 = sb + lane * 4 + v * 1280;
        const uint32_t vp = t8 + v * 1280 + ((lane >> 3) & 1) * 640 + ((lane >> 4) ? SM_SC + 384 : SM_VB + 512);
        const uint32_t vx = t8 + SM_VB + v * 1280 + ((lane >> 3) & 1) * 640 + (lane >> 4) * 128;
        PIN2(vx, vp)
        if (v == 0) {
            if (X_AT) spin_until(t_s, X_AT);
            if (elect_one()) { issue_x(sb, tm_x, s + 1, 0); issue_x(sb, tm_x, s + 1, 1); }
            __syncwarp();
            SCHED_FENCE
            bar_sync(NB_XR, 384);
        } else {
            uint32_t ka[16], qb[8], qc[8];
            float s0[4] = {0.f, 0.f, 0.f, 0.f}, s1[4] = {0.f, 0.f, 0.f, 0.f}, s2[4] = {0.f, 0.f, 0.f, 0.f}, s3[4] = {0.f, 0.f, 0.f, 0.f};
            const uint32_t xo = sb + SM_XIN + rank * 640 + (v - 1) * 256 + lane * 4;
            const uint32_t x1 = xo + d1, x2 = xo + d2, b1 = xb + d1 + (tid >> 10), b2 = xb + d2 + (tid >> 10), b0 = xb + (tid >> 10);
            PIN2(x1, x2) PIN2(b1, b2) PIN2(xo, b0)
#define SC_MMA \
            mma16816(s0, ka[0], ka[1], ka[2], ka[3], qb[0], qb[1]); SCHED_FENCE mma16816(s1, ka[4], ka[5], ka[6], ka[7], qb[2], qb[3]); SCHED_FENCE \
            mma16816(s2, ka[0], ka[1], ka[2], ka[3], qc[0], qc[1]); SCHED_FENCE mma16816(s3, ka[4], ka[5], ka[6], ka[7], qc[2], qc[3]); SCHED_FENCE \
            mma16816(s0, ka[8], ka[9], ka[10], ka[11], qb[4], qb[5]); SCHED_FENCE mma16816(s1, ka[12], ka[13], ka[14], ka[15], qb[6], qb[7]); SCHED_FENCE \
            mma16816(s2, ka[8], ka[9], ka[10], ka[11], qc[4], qc[5]); SCHED_FENCE mma16816(s3, ka[12], ka[13], ka[14], ka[15], qc[6], qc[7]); SCHED_FENCE
            if (v < 3) {
                const uint32_t aa = t8 + SM_KB + (lane >> 4) * 640 + ((lane >> 3) & 1) * 128 + (v - 1) * 256;
#pragma unroll
                for (int ks = 0; ks < 4; ks++) LD_T(&ka[4 * ks], aa + ks * 1280)
                SCHED_FENCE
                bar_sync(NB_XR, 384);
                LD_T(&qb[0], qq) SCHED_FENCE LD_T(&qc[0], qq + 128) SCHED_FENCE LD_T(&qb[4], qq + 2560) SCHED_FENCE LD_T(&qc[4], qq + 2560 + 128)
                SCHED_FENCE
                SC_MMA
                const uint32_t q0 = pack_bf16((s0[0] + s1[0]) + (s2[0] + s3[0]), (s0[1] + s1[1]) + (s2[1] + s3[1]));
                const uint32_t q1 = pack_bf16((s0[2] + s1[2]) + (s2[2] + s3[2]), (s0[3] + s1[3]) + (s2[3] + s3[3]));
                st_async1(x1, q0, b1); st_async1(x2, q0, b2); st_async1(x1 + 128, q1, b1); st_async1(x2 + 128, q1, b2);
                st_async1(xo, q0, b0); st_async1(xo + 128, q1, b0);
            } else {
                const uint32_t aa = t8 + (lane >> 4) * 640 + (((lane >> 3) & 1) ? SM_SC + 256 : SM_KB + 512);
                PIN1(aa)
                SCHED_FENCE
                bar_sync(NB_XR, 384);
                LD_T(&ka[0], aa) SCHED_FENCE LD_T(&qb[0], qq) SCHED_FENCE LD_T(&ka[4], aa + 1280) SCHED_FENCE LD_T(&qc[0], qq + 128) SCHED_FENCE
                LD_T(&ka[8], aa + 2 * 1280) SCHED_FENCE LD_T(&qb[4], qq + 2560) SCHED_FENCE LD_T(&ka[12], aa + 3 * 1280) SCHED_FENCE LD_T(&qc[4], qq + 2560 + 128)
                SCHED_FENCE
                SC_MMA
                const uint32_t q0 = pack_bf16((((s0[0] + s0[2]) + (s1[0] + s1[2])) + (s2[0] + s2[2])) + (s3[0] + s3[2]), (((s0[1] + s0[3]) + (s1[1] + s1[3])) + (s2[1] + s2[3])) + (s3[1] + s3[3]));
                st_async1(x1, q0, b1); st_async1(x2, q0, b2); st_async1(xo, q0, b0);
            }
#undef SC_MMA
        }
        uint32_t va[8], vm[4];
        ldsm4(va[0], va[1], va[2], va[3], vx);
        ldsm4(va[4], va[5], va[6], va[7], vx + 256);
        ldsm4(vm[0], vm[1], vm[2], vm[3], vp);
        bar_arrive(NB_QK, 384);
        const uint32_t oa = sb + SM_WO + ((lane >> 4) * 8 + (lane & 7)) * 128 + (((2 * v + ((lane >> 3) & 1)) ^ (lane & 7)) << 4);
        if (s == 0) { mbar_wait(sb + SM_BAR + MB_W2, 0); LD_O(A, oa + 9 * 8192) }
        uint32_t pb[5];
        const uint32_t ow = oa + rank * (3 * 8192);
        const uint32_t dd = (own0 - rank) << 24;
        const uint32_t id = sb + dd + SM_MEM + ((own0 + 2u - rank) % 3u) * 4096 + v * 256 + lane * 8, ib = sb + dd + SM_IB + v * 8 + (tid >> 10);
        {
            PIN2(ow, id) PIN1(ib) PIN2(xi, l4)
            SCHED_FENCE
            mbar_wait(xb, s & 1);
            uint32_t u[16];
            LD_T(&u[0], xi) LD_T(&u[4], xi + 512) LD_T(&u[8], xi + 1024) LD_T(&u[12], xi + 1536)
            float p[10];
#pragma unroll
            for (int n = 0; n < 5; n++) {
                p[2 * n] = bf_lo(u[n]) + bf_lo(u[5 + n]) + bf_lo(u[10 + n]);
                p[2 * n + 1] = bf_hi(u[n]) + bf_hi(u[5 + n]) + bf_hi(u[10 + n]);
            }
            const float ml = fmaxf(fmaxf(fmaxf(fmaxf(p[0], p[1]), fmaxf(p[2], p[3])), fmaxf(p[4], p[5])), fmaxf(fmaxf(p[6], p[7]), fmaxf(p[8], p[9])));
            const float m1 = __shfl_xor_sync(0xffffffffu, ml, 1), m2 = __shfl_xor_sync(0xffffffffu, ml, 2), m3 = __shfl_xor_sync(0xffffffffu, ml, 3);
            const float mb = ml * SCALE_A;
#pragma unroll
            for (int i = 0; i < 10; i++) p[i] = ex2(fmaf(p[i], SCALE_A, -mb));
            const float cr = ex2(fmaf(fmaxf(fmaxf(ml, m1), fmaxf(m2, m3)), -SCALE_A, mb));
#pragma unroll
            for (int i = 0; i < 5; i++) pb[i] = pack_bf16(p[2 * i] * cr, p[2 * i + 1] * cr);
            float o[4] = {0.f, 0.f, 0.f, 0.f}, o2[4] = {0.f, 0.f, 0.f, 0.f};
            mma16816(o, va[0], va[1], va[2], va[3], pb[0], pb[1]);
            mma16816(o2, va[4], va[5], va[6], va[7], pb[2], pb[3]);
            mma16816(o, vm[0], vm[1], vm[2], vm[3], pb[4], pb[4]);
            sts32(l4 + SM_SC, pack_bf16(o[0] + o2[0], o[1] + o2[1]));
            sts32(l4 + SM_SC + 640, pack_bf16(o[2] + o2[2], o[3] + o2[3]));
        }
        SCHED_FENCE
        bar_sync(NB_O, 384);
        const unsigned t_o = clk32() + (lane >> 16);
        {
            float z[4] = {0.f, 0.f, 0.f, 0.f}, z2[4] = {0.f, 0.f, 0.f, 0.f}, z3[4] = {0.f, 0.f, 0.f, 0.f};
            mma16816(z, 0x3F803F80u, 0x3F803F80u, 0x3F803F80u, 0x3F803F80u, pb[0], pb[1]);
            mma16816(z2, 0x3F803F80u, 0x3F803F80u, 0x3F803F80u, 0x3F803F80u, pb[2], pb[3]);
            mma1688(z3, 0x3F803F80u, 0x3F803F80u, pb[4]);
            SCHED_FENCE
            uint32_t B[8], A2[16], A3[16], A4[16];
            ldsm4t(B[0], B[1], B[2], B[3], qq);
            SCHED_FENCE
            ldsm4t(B[4], B[5], B[6], B[7], qq + 2560);
            SCHED_FENCE
            LD_T(&A2[0], ow) SCHED_FENCE LD_T(&A2[4], ow + 2048) SCHED_FENCE
            const float i0 = rcp(z[0] + z2[0] + z3[0]), i1 = rcp(z[1] + z2[1] + z3[1]);
            asm volatile("" :: "f"(i0), "f"(i1));
            SCHED_FENCE
            float f[4][4], c2[4] = {0.f, 0.f, 0.f, 0.f};
#pragma unroll
            for (int i = 0; i < 4; i++) { f[i][0] = f[i][1] = f[i][2] = f[i][3] = 0.f; }
            MMA_K(f[0], A, 0) MMA_K(c2, A, 1)
            SCHED_FENCE
            MMA_K(f[0], A, 2) MMA_K(c2, A, 3)
            f[0][0] += c2[0]; f[0][1] += c2[1]; f[0][2] += c2[2]; f[0][3] += c2[3];
            if (!mine0) st_async2(id, pack_bf16(f[0][0], f[0][1]), pack_bf16(f[0][2], f[0][3]), ib);
            SCHED_FENCE
            LD_T(&A3[0], ow + 8192) SCHED_FENCE LD_T(&A4[0], ow + 2 * 8192) SCHED_FENCE LD_T(&A3[4], ow + 8192 + 2048) SCHED_FENCE LD_T(&A4[4], ow + 2 * 8192 + 2048) SCHED_FENCE
            LD_T(&A2[8], ow + 2 * 2048) SCHED_FENCE
            MMA_K(f[1], A2, 0) SCHED_FENCE LD_T(&A3[8], ow + 8192 + 2 * 2048) SCHED_FENCE
            MMA_K(f[1], A2, 1) SCHED_FENCE LD_T(&A4[8], ow + 2 * 8192 + 2 * 2048) SCHED_FENCE
            MMA_K(f[2], A3, 0) SCHED_FENCE MMA_K(f[3], A4, 0) SCHED_FENCE
            MMA_K(f[2], A3, 1) SCHED_FENCE LD_T(&A2[12], ow + 3 * 2048) SCHED_FENCE
            MMA_K(f[3], A4, 1) SCHED_FENCE LD_T(&A3[12], ow + 8192 + 3 * 2048) SCHED_FENCE
            MMA_K(f[1], A2, 2) SCHED_FENCE LD_T(&A4[12], ow + 2 * 8192 + 3 * 2048) SCHED_FENCE
            MMA_K(f[2], A3, 2) SCHED_FENCE MMA_K(f[3], A4, 2) SCHED_FENCE
            MMA_K(f[1], A2, 3) SCHED_FENCE MMA_K(f[2], A3, 3) SCHED_FENCE MMA_K(f[3], A4, 3) SCHED_FENCE
            const uint64_t g00 = RS_AD(0, 0), g01 = RS_AD(0, 1), g10 = RS_AD(1, 0), g11 = RS_AD(1, 1), g20 = RS_AD(2, 0), g21 = RS_AD(2, 1), g30 = RS_AD(3, 0), g31 = RS_AD(3, 1);
            PINL(g00) PINL(g01) PINL(g10) PINL(g11) PINL(g20) PINL(g21) PINL(g30) PINL(g31)
            const uint32_t tag = par ^ 1u, in = sb + SM_MEM + v * 256 + lane * 8;
            const uint32_t eye = ((lane >> 2) == 2 * (lane & 3) ? 0x3F80u : 0u) | ((lane >> 2) == 2 * (lane & 3) + 1 ? 0x3F800000u : 0u);
            PIN2(tag, in) PIN1(eye)
#define O_LD(i) const uint2 x##i = lds64(in + (i) * 1024), y##i = lds64(in + (i) * 1024 + 4096);
#define O_ADD(i) mma16816(f[i], x##i.x, x##i.y, y##i.x, y##i.y, eye, eye);
#define O_PUT(i) { st_relaxed1_a<RS_OF(i, 0)>(g##i##0, lop3<0xE4>(tag, pack_bf16(f[i][0] * i0, f[i][1] * i1), 1u)); \
                   st_relaxed1_a<RS_OF(i, 1)>(g##i##1, lop3<0xE4>(tag, pack_bf16(f[i][2] * i0, f[i][3] * i1), 1u)); }
            SCHED_FENCE
            mbar_wait(sb + SM_IB + v * 8, s & 1);
            O_LD(1) O_LD(2) O_LD(0)
            O_ADD(1) O_ADD(2) O_ADD(0)
            O_PUT(1) O_PUT(2)
            if (mine0) O_PUT(0)
            mbar_wait(sb + SM_IB + 32 + v * 8, s & 1);
            O_LD(3) O_ADD(3) O_PUT(3)
#undef O_LD
#undef O_ADD
#undef O_PUT
            bar_arrive(NB_TS, 384);
        }
#undef RS_AD
#undef RS_OF
        bar_sync(NB_WG2, 128);
        const int tq = opaque(tid0);
        const uint32_t ntag = par - 1u;
        unsigned t_a = t_o + ag_at;
        if (__builtin_expect(blockIdx.x < NRED, 1)) {
            const char* q0 = (const char*)mk64(ro + v * 1024 + (tq & 31) * 4, ghi);
            constexpr int ST = 128;
            const uint64_t pub = mk64((po + (tq & 7) * 4) ^ ((tq & 8) << 9), ghi);
            const uint32_t keep = (tq & 3) == 0 ? 1u : 0u;
            PINL(q0) PINL(pub) PIN2(ntag, keep)
#define RS_LD(L, q) { L[0] = ld_relaxed1_off<0>(q); L[1] = ld_relaxed1_off<ST>(q); L[2] = ld_relaxed1_off<2 * ST>(q); L[3] = ld_relaxed1_off<3 * ST>(q); \
                      L[4] = ld_relaxed1_off<4 * ST>(q); L[5] = ld_relaxed1_off<5 * ST>(q); L[6] = ld_relaxed1_off<6 * ST>(q); L[7] = ld_relaxed1_off<7 * ST>(q); }
            spin_until(t_o, rs_at);
            int n = 0;
#pragma unroll 1
            while (true) {
                uint32_t L[8], M[8];
                RS_LD(L, q0)
                uint32_t ql = __shfl_sync(0xffffffffu, (uint32_t)(uintptr_t)q0, tq);
#pragma unroll
                for (int i = 0; i < RS_CH; i++) asm volatile("brev.b32 %0, %0;\nbrev.b32 %0, %0;" : "+r"(ql));
                const char* q1 = (const char*)mk64(ql, ghi);
                RS_LD(M, q1)
                if (rs_try(L, ntag, keep, pub, tq & 16)) break;
                n++;
                if (rs_try(M, ntag, keep, pub, tq & 16) || ++n > SPIN_MAX / 64) break;
            }
            if (PAUSE) bar_arrive(NB_PUB, 384);
            t_a = clk32() + ag_d;
#undef RS_LD
            err |= n;
        } else if (PAUSE) {
            bar_arrive(NB_PUB, 384);
        }
        const char* a0 = (const char*)mk64(ao0 + tq * 16, ghi);
        const char* a1 = (const char*)mk64(ao1 + tq * 16, ghi);
        const char* a2 = (const char*)mk64(ao2 + tq * 16, ghi);
        const uint32_t md = sb + SM_MEM + tq * 16;
        PINL(a0) PINL(a1) PINL(a2) PIN1(md)
        spin_until(t_o, t_a - t_o);
        {
            int n = 0;
            uint4 w0 = AG_LD(a0), w1 = AG_LD(a0 + 2048), w2 = AG_LD(a1), w3 = AG_LD(a1 + 2048), w4 = AG_LD(a2);
            sts128(md, w0); sts128(md + 2048, w1); sts128(md + 4096, w2); sts128(md + 6144, w3); sts128(md + 8192, w4);
#pragma unroll 1
            while (__builtin_expect(__any_sync(0xffffffffu, lop3<0xA8>(lop3<0x7E>(w0.x, w1.x, ntag) | lop3<0x7E>(w2.x, w3.x, ntag), w4.x ^ ntag, 1u) != 0u), 0) && ++n <= SPIN_MAX / 64) {
                const bool b0 = (w0.x ^ ntag) & 1u, b1 = (w1.x ^ ntag) & 1u, b2 = (w2.x ^ ntag) & 1u, b3 = (w3.x ^ ntag) & 1u, b4 = (w4.x ^ ntag) & 1u;
                ag_ld_if(w0, a0, b0); ag_ld_if(w1, a0 + 2048, b1); ag_ld_if(w2, a1, b2); ag_ld_if(w3, a1 + 2048, b3); ag_ld_if(w4, a2, b4);
                sts128_if(md, w0, b0); sts128_if(md + 2048, w1, b1); sts128_if(md + 4096, w2, b2); sts128_if(md + 6144, w3, b3); sts128_if(md + 8192, w4, b4);
            }
            err |= n;
        }
        bar_sync(NB_ALL, 384);
    }
    if (err > SPIN_MAX / 64) g_err = 3;
    if (tid == 0) st_relaxed1(&g_side[blockIdx.x * 8], 0u);
}

__global__ void __cluster_dims__(3, 1, 1) __launch_bounds__(384, 1)
rec_kernel(const __grid_constant__ CUtensorMap tm_x, const __grid_constant__ CUtensorMap tm_wq, const __grid_constant__ CUtensorMap tm_wk,
           const __grid_constant__ CUtensorMap tm_wv, const __grid_constant__ CUtensorMap tm_wo, const bf16* __restrict__ mem0) {
    extern __shared__ __align__(1024) char smem_raw[];
    const uint32_t sb = smem_u32(smem_raw);
    uint32_t rank; asm volatile("mov.u32 %0, %%cluster_ctarank;" : "=r"(rank));
    const int head = blockIdx.x / 3;
    if (threadIdx.x == 0) {
        if ((sb & 0x3FFFF) != SB0 || mapa(sb, 0) + (rank << 24) != sb || mapa(sb, 2) - mapa(sb, 1) != (1u << 24)) __trap();
        mbar_init(sb + SM_BAR + MB_W0, 1); mbar_init(sb + SM_BAR + MB_W1, 1); mbar_init(sb + SM_BAR + MB_W2, 1);
        mbar_init(sb + SM_BAR + MB_G, 1); mbar_init(sb + SM_BAR + MB_G + 8, 1); mbar_init(sb + SM_BAR + MB_X, 1);
        for (int i = 0; i < 8; i++) mbar_init(sb + SM_IB + 8 * i, 1);
        asm volatile("fence.mbarrier_init.release.cluster;" ::: "memory");
        mbar_expect(sb + SM_BAR + MB_W0, 163840);
    }
    __syncthreads();
    asm volatile("barrier.cluster.arrive.release;" ::: "memory");
    if (threadIdx.x == 0) { const uint64_t pol = pol_stream(); for (int i = 0; i < 5; i++) tma2d_s(sb + SM_WO + i * 16384, &tm_wk, head * DH + rank * 64, i * 128, sb + SM_BAR + MB_W0, pol); }
    if (threadIdx.x == 32) { const uint64_t pol = pol_stream(); for (int i = 0; i < 5; i++) tma2d_s(sb + SM_WQ + i * 16384, &tm_wv, head * DH + rank * 64, i * 128, sb + SM_BAR + MB_W0, pol); }
    if (threadIdx.x == 64) { issue_x(sb, &tm_x, 0, 0); issue_x(sb, &tm_x, 0, 1); }
    if (threadIdx.x == 96) for (int i = 0; i < 5; i++) tma2d_prefetch(&tm_wq, head * DH + rank * 64, i * 128);
    if (threadIdx.x == 128) for (int i = 0; i < 10; i++) tma2d_prefetch(&tm_wo, i * 64, head * DH + rank * 64);
    if (blockIdx.x == 0) {
        for (int i = threadIdx.x; i < (int)(sizeof(AuxCtl) / 16); i += 384) ((uint4*)&g_ctl)[i] = make_uint4(0u, 0u, 0u, 0u);
        __threadfence();
    }
    __syncthreads();
    asm volatile("griddepcontrol.launch_dependents;" ::: "memory");
    const int wg = __shfl_sync(0xffffffffu, vtid() >> 7, 0);
    if (wg == 0) {
        asm volatile("setmaxnreg.inc.sync.aligned.u32 %0;" :: "n"(R_WG0));
        rec_weights<0>(sb, rank, &tm_x, &tm_wq, &tm_wo, head);
        cluster_sync();
    } else if (wg == 1) {
        asm volatile("setmaxnreg.inc.sync.aligned.u32 %0;" :: "n"(R_WG0));
        rec_weights<1>(sb, rank, &tm_x, &tm_wq, &tm_wo, head);
        cluster_sync();
    } else {
        asm volatile("setmaxnreg.dec.sync.aligned.u32 %0;" :: "n"(R_WG2));
        rec_comm(sb, rank, mem0, &tm_x, head);
        cluster_sync();
    }
}

#define B_AHEAD 3
#define PF_AHEAD 14
#define EVF 15
#define REQ_AHEAD 7
constexpr uint32_t RING_CAP = 176 * 1024;
constexpr uint32_t SZ_G = 32768, SZ_Q = 40960, SZ_KV = 30720, SZ_B = 27648, SZ_QP = 49152;
#define QPRE 15
constexpr uint32_t G_OUT = RING_CAP, STG_BYTES = 24576;
constexpr uint32_t GEMM_SMEM = G_OUT + 2 * STG_BYTES + 512;

#define ACC64(d) ACC16(d), ACC16((d + 16)), ACC16((d + 32)), ACC16((d + 48))
__device__ __forceinline__ void wgmma_ss_n128_tb(float* d, uint64_t da, uint64_t db, int acc) {
    asm volatile("{\n.reg .pred p;\nsetp.ne.b32 p, %66, 0;\n"
                 "wgmma.mma_async.sync.aligned.m64n128k16.f32.bf16.bf16 "
                 "{%0,%1,%2,%3,%4,%5,%6,%7,%8,%9,%10,%11,%12,%13,%14,%15,%16,%17,%18,%19,%20,%21,%22,%23,%24,%25,%26,%27,%28,%29,%30,%31,"
                 "%32,%33,%34,%35,%36,%37,%38,%39,%40,%41,%42,%43,%44,%45,%46,%47,%48,%49,%50,%51,%52,%53,%54,%55,%56,%57,%58,%59,%60,%61,%62,%63}, "
                 "%64, %65, p, 1, 1, 0, 1;\n}"
                 : ACC64(d) : "l"(da), "l"(db), "r"(acc));
}

__device__ __forceinline__ void wgmma_ss_n192_tb(float* d, uint64_t da, uint64_t db, int acc) {
    asm volatile("{\n.reg .pred p;\nsetp.ne.b32 p, %98, 0;\n"
                 "wgmma.mma_async.sync.aligned.m64n192k16.f32.bf16.bf16 "
                 "{%0,%1,%2,%3,%4,%5,%6,%7,%8,%9,%10,%11,%12,%13,%14,%15,%16,%17,%18,%19,%20,%21,%22,%23,%24,%25,%26,%27,%28,%29,%30,%31,"
                 "%32,%33,%34,%35,%36,%37,%38,%39,%40,%41,%42,%43,%44,%45,%46,%47,%48,%49,%50,%51,%52,%53,%54,%55,%56,%57,%58,%59,%60,%61,%62,%63,"
                 "%64,%65,%66,%67,%68,%69,%70,%71,%72,%73,%74,%75,%76,%77,%78,%79,%80,%81,%82,%83,%84,%85,%86,%87,%88,%89,%90,%91,%92,%93,%94,%95}, "
                 "%96, %97, p, 1, 1, 0, 1;\n}"
                 : ACC64(d), ACC16((d + 64)), ACC16((d + 80)) : "l"(da), "l"(db), "r"(acc));
}

__device__ __forceinline__ void wgmma_ss_n128_tb_first(float* d, uint64_t da, uint64_t db) {
    asm volatile("wgmma.mma_async.sync.aligned.m64n128k16.f32.bf16.bf16 {%0,%1,%2,%3,%4,%5,%6,%7,%8,%9,%10,%11,%12,%13,%14,%15,%16,%17,%18,%19,%20,%21,%22,%23,%24,%25,%26,%27,%28,%29,%30,%31,%32,%33,%34,%35,%36,%37,%38,%39,%40,%41,%42,%43,%44,%45,%46,%47,%48,%49,%50,%51,%52,%53,%54,%55,%56,%57,%58,%59,%60,%61,%62,%63}, %64, %65, 0, 1, 1, 0, 1;"
                 : "=f"(d[0]), "=f"(d[1]), "=f"(d[2]), "=f"(d[3]), "=f"(d[4]), "=f"(d[5]), "=f"(d[6]), "=f"(d[7]), "=f"(d[8]), "=f"(d[9]), "=f"(d[10]), "=f"(d[11]), "=f"(d[12]), "=f"(d[13]), "=f"(d[14]), "=f"(d[15]), "=f"(d[16]), "=f"(d[17]), "=f"(d[18]), "=f"(d[19]), "=f"(d[20]), "=f"(d[21]), "=f"(d[22]), "=f"(d[23]), "=f"(d[24]), "=f"(d[25]), "=f"(d[26]), "=f"(d[27]), "=f"(d[28]), "=f"(d[29]), "=f"(d[30]), "=f"(d[31]), "=f"(d[32]), "=f"(d[33]), "=f"(d[34]), "=f"(d[35]), "=f"(d[36]), "=f"(d[37]), "=f"(d[38]), "=f"(d[39]), "=f"(d[40]), "=f"(d[41]), "=f"(d[42]), "=f"(d[43]), "=f"(d[44]), "=f"(d[45]), "=f"(d[46]), "=f"(d[47]), "=f"(d[48]), "=f"(d[49]), "=f"(d[50]), "=f"(d[51]), "=f"(d[52]), "=f"(d[53]), "=f"(d[54]), "=f"(d[55]), "=f"(d[56]), "=f"(d[57]), "=f"(d[58]), "=f"(d[59]), "=f"(d[60]), "=f"(d[61]), "=f"(d[62]), "=f"(d[63]) : "l"(da), "l"(db));
}
__device__ __forceinline__ void wgmma_ss_n192_tb_first(float* d, uint64_t da, uint64_t db) {
    asm volatile("wgmma.mma_async.sync.aligned.m64n192k16.f32.bf16.bf16 {%0,%1,%2,%3,%4,%5,%6,%7,%8,%9,%10,%11,%12,%13,%14,%15,%16,%17,%18,%19,%20,%21,%22,%23,%24,%25,%26,%27,%28,%29,%30,%31,%32,%33,%34,%35,%36,%37,%38,%39,%40,%41,%42,%43,%44,%45,%46,%47,%48,%49,%50,%51,%52,%53,%54,%55,%56,%57,%58,%59,%60,%61,%62,%63,%64,%65,%66,%67,%68,%69,%70,%71,%72,%73,%74,%75,%76,%77,%78,%79,%80,%81,%82,%83,%84,%85,%86,%87,%88,%89,%90,%91,%92,%93,%94,%95}, %96, %97, 0, 1, 1, 0, 1;"
                 : "=f"(d[0]), "=f"(d[1]), "=f"(d[2]), "=f"(d[3]), "=f"(d[4]), "=f"(d[5]), "=f"(d[6]), "=f"(d[7]), "=f"(d[8]), "=f"(d[9]), "=f"(d[10]), "=f"(d[11]), "=f"(d[12]), "=f"(d[13]), "=f"(d[14]), "=f"(d[15]), "=f"(d[16]), "=f"(d[17]), "=f"(d[18]), "=f"(d[19]), "=f"(d[20]), "=f"(d[21]), "=f"(d[22]), "=f"(d[23]), "=f"(d[24]), "=f"(d[25]), "=f"(d[26]), "=f"(d[27]), "=f"(d[28]), "=f"(d[29]), "=f"(d[30]), "=f"(d[31]), "=f"(d[32]), "=f"(d[33]), "=f"(d[34]), "=f"(d[35]), "=f"(d[36]), "=f"(d[37]), "=f"(d[38]), "=f"(d[39]), "=f"(d[40]), "=f"(d[41]), "=f"(d[42]), "=f"(d[43]), "=f"(d[44]), "=f"(d[45]), "=f"(d[46]), "=f"(d[47]), "=f"(d[48]), "=f"(d[49]), "=f"(d[50]), "=f"(d[51]), "=f"(d[52]), "=f"(d[53]), "=f"(d[54]), "=f"(d[55]), "=f"(d[56]), "=f"(d[57]), "=f"(d[58]), "=f"(d[59]), "=f"(d[60]), "=f"(d[61]), "=f"(d[62]), "=f"(d[63]), "=f"(d[64]), "=f"(d[65]), "=f"(d[66]), "=f"(d[67]), "=f"(d[68]), "=f"(d[69]), "=f"(d[70]), "=f"(d[71]), "=f"(d[72]), "=f"(d[73]), "=f"(d[74]), "=f"(d[75]), "=f"(d[76]), "=f"(d[77]), "=f"(d[78]), "=f"(d[79]), "=f"(d[80]), "=f"(d[81]), "=f"(d[82]), "=f"(d[83]), "=f"(d[84]), "=f"(d[85]), "=f"(d[86]), "=f"(d[87]), "=f"(d[88]), "=f"(d[89]), "=f"(d[90]), "=f"(d[91]), "=f"(d[92]), "=f"(d[93]), "=f"(d[94]), "=f"(d[95]) : "l"(da), "l"(db));
}

__device__ __forceinline__ void mma16816_n(float* c, uint32_t a0, uint32_t a1, uint32_t a2, uint32_t a3, uint32_t b0, uint32_t b1) {
    asm("mma.sync.aligned.m16n8k16.row.col.f32.bf16.bf16.f32 {%0,%1,%2,%3}, {%4,%5,%6,%7}, {%8,%9}, {%0,%1,%2,%3};"
        : "+f"(c[0]), "+f"(c[1]), "+f"(c[2]), "+f"(c[3]) : "r"(a0), "r"(a1), "r"(a2), "r"(a3), "r"(b0), "r"(b1));
}
__device__ __forceinline__ void mma1688_n(float* c, uint32_t a0, uint32_t a1, uint32_t b0) {
    asm("mma.sync.aligned.m16n8k8.row.col.f32.bf16.bf16.f32 {%0,%1,%2,%3}, {%4,%5}, {%6}, {%0,%1,%2,%3};"
        : "+f"(c[0]), "+f"(c[1]), "+f"(c[2]), "+f"(c[3]) : "r"(a0), "r"(a1), "r"(b0));
}
constexpr uint32_t B_PITCH = 336;
__device__ __forceinline__ uint32_t lds32_n(uint32_t a) { uint32_t v; asm("ld.shared.u32 %0, [%1];" : "=r"(v) : "r"(a)); return v; }
__device__ __forceinline__ uint32_t lds16_n(uint32_t a) { unsigned short v; asm("ld.shared.u16 %0, [%1];" : "=h"(v) : "r"(a)); return v; }
template <bool EDGE>
__device__ __forceinline__ void attnB_scores(uint32_t dq, uint32_t dk, int i, int tok0, int lane, uint32_t (&pa)[8]) {
    const int g = lane >> 2, t = lane & 3;
    const uint32_t qa = dq + (16 * i + 14 + g) * B_PITCH + 4 * t;
    const uint32_t a0 = lds32_n(qa), a1 = lds32_n(qa + 8 * B_PITCH), a2 = lds32_n(qa + 16), a3 = lds32_n(qa + 8 * B_PITCH + 16);
    const uint32_t e0 = t < 2 ? lds32_n(qa + 32) : 0u, e1 = t < 2 ? lds32_n(qa + 8 * B_PITCH + 32) : 0u;
    float sc[4][4];
#pragma unroll
    for (int n = 0; n < 4; n++) {
        const uint32_t ka = dk + (16 * i + 8 * n + g) * B_PITCH + 4 * t;
        const uint32_t b0 = lds32_n(ka), b1 = lds32_n(ka + 16), b2 = t < 2 ? lds32_n(ka + 32) : 0u;
        sc[n][0] = sc[n][1] = sc[n][2] = sc[n][3] = 0.f;
        mma16816_n(sc[n], a0, a1, a2, a3, b0, b1);
        mma1688_n(sc[n], e0, e1, b2);
    }
    const int odd = g & 1, e = g - 2 * t - odd + 14;
    float v0[4], v1[4];
    float m0 = -3.0e38f, m1 = -3.0e38f;
#pragma unroll
    for (int n = 0; n < 4; n++) {
        const int d0 = e - 8 * n, d1 = d0 + 8;
        const bool ok0 = d0 >= 0 && d0 <= 14 && (!EDGE || tok0 + 16 * i + g - d0 >= 0), ok1 = d1 >= 0 && d1 <= 14 && (!EDGE || tok0 + 16 * i + g + 8 - d1 >= 0);
        v0[n] = ok0 ? (odd ? sc[n][1] : sc[n][0]) : -3.0e38f;
        v1[n] = ok1 ? (odd ? sc[n][3] : sc[n][2]) : -3.0e38f;
        m0 = fmaxf(m0, v0[n]); m1 = fmaxf(m1, v1[n]);
    }
    m0 = fmaxf(m0, __shfl_xor_sync(0xffffffffu, m0, 1)); m1 = fmaxf(m1, __shfl_xor_sync(0xffffffffu, m1, 1));
    m0 = fmaxf(m0, __shfl_xor_sync(0xffffffffu, m0, 2)); m1 = fmaxf(m1, __shfl_xor_sync(0xffffffffu, m1, 2));
    const float scl = 0.22360679774997896f * 1.4426950408889634f;
    m0 *= scl; m1 *= scl;
    float s0 = 0.f, s1 = 0.f;
#pragma unroll
    for (int n = 0; n < 4; n++) {
        v0[n] = ex2(fmaf(fmaxf(v0[n], -1.0e30f), scl, -m0)); v1[n] = ex2(fmaf(fmaxf(v1[n], -1.0e30f), scl, -m1));
        s0 += v0[n]; s1 += v1[n];
    }
    s0 += __shfl_xor_sync(0xffffffffu, s0, 1); s1 += __shfl_xor_sync(0xffffffffu, s1, 1);
    s0 += __shfl_xor_sync(0xffffffffu, s0, 2); s1 += __shfl_xor_sync(0xffffffffu, s1, 2);
    const float i0 = rcp(s0), i1 = rcp(s1);
    const int sh = odd * 16;
#pragma unroll
    for (int k = 0; k < 2; k++) {
        pa[4 * k] = (pack_bf16(v0[2 * k] * i0, 0.f) & 0xffffu) << sh; pa[4 * k + 1] = (pack_bf16(v1[2 * k] * i1, 0.f) & 0xffffu) << sh;
        pa[4 * k + 2] = (pack_bf16(v0[2 * k + 1] * i0, 0.f) & 0xffffu) << sh; pa[4 * k + 3] = (pack_bf16(v1[2 * k + 1] * i1, 0.f) & 0xffffu) << sh;
    }
}
__device__ __forceinline__ void attnB_pv(uint32_t dv, int i, int lane, const uint32_t (&pa)[8], uint32_t (&ob)[6]) {
    const int g = lane >> 2, t = lane & 3;
#pragma unroll
    for (int n = 0; n < 3; n++) {
        float o[4] = {0.f, 0.f, 0.f, 0.f};
#pragma unroll
        for (int k = 0; k < 2; k++) {
            const uint32_t va = dv + (16 * i + 16 * k + 2 * t) * B_PITCH + (8 * n + g) * 2;
            const uint32_t b0 = lds16_n(va) | (lds16_n(va + B_PITCH) << 16), b1 = lds16_n(va + 8 * B_PITCH) | (lds16_n(va + 9 * B_PITCH) << 16);
            mma16816_n(o, pa[4 * k], pa[4 * k + 1], pa[4 * k + 2], pa[4 * k + 3], b0, b1);
        }
        ob[2 * n] = pack_bf16(o[0], o[1]); ob[2 * n + 1] = pack_bf16(o[2], o[3]);
    }
}
__device__ __forceinline__ void gate8(int tok0, int lane, const bf16* __restrict__ x, const bf16* __restrict__ gate_w) {
    uint2 u[8][5], g[5];
#pragma unroll
    for (int i = 0; i < 5; i++) asm volatile("ld.global.nc.v2.u32 {%0,%1}, [%2];" : "=r"(g[i].x), "=r"(g[i].y) : "l"(gate_w + lane * 20 + 4 * i));
#pragma unroll
    for (int j = 0; j < 8; j++)
#pragma unroll
        for (int i = 0; i < 5; i++)
            asm volatile("ld.global.nc.v2.u32 {%0,%1}, [%2];" : "=r"(u[j][i].x), "=r"(u[j][i].y) : "l"(x + (size_t)(tok0 + j) * DM + lane * 20 + 4 * i));
    asm volatile("" ::: "memory");
    float mine = 0.f;
#pragma unroll
    for (int j = 0; j < 8; j++) {
        float a = 0.f;
#pragma unroll
        for (int i = 0; i < 5; i++) {
            a += __bfloat162float(__float2bfloat16(bf_lo(u[j][i].x) * bf_lo(g[i].x))); a += __bfloat162float(__float2bfloat16(bf_hi(u[j][i].x) * bf_hi(g[i].x)));
            a += __bfloat162float(__float2bfloat16(bf_lo(u[j][i].y) * bf_lo(g[i].y))); a += __bfloat162float(__float2bfloat16(bf_hi(u[j][i].y) * bf_hi(g[i].y)));
        }
#pragma unroll
        for (int o2 = 16; o2 > 0; o2 >>= 1) a += __shfl_xor_sync(0xffffffffu, a, o2);
        if (lane == j) mine = a;
    }
    if (lane < 8) {
        const float a = __bfloat162float(__float2bfloat16(mine));
        g_gate[tok0 + lane] = __bfloat162float(__float2bfloat16(1.f / (1.f + __expf(-a))));
    }
}

#define NFULL 5
#define SPL_MID 2
#define SPL_14 3
#define SPL_LAST 8
__host__ __device__ constexpr int spl(int g) { return g < NFULL ? 1 : g < 14 ? SPL_MID : g == 14 ? SPL_14 : SPL_LAST + 1; }
__host__ __device__ constexpr int slab0(int g) { int n = 0; for (int i = NFULL; i < g; i++) n += spl(i); return n; }
static_assert(slab0(16) <= 96, "g_part");
struct Item { int type, mb, nb, k0, nk, half, bpart, slab; };
__host__ __device__ constexpr uint32_t mk_item(int type, int mb, int nb, int k0, int nk, int half) {
    return (uint32_t)type | ((uint32_t)mb << 3) | ((uint32_t)nb << 7) | ((uint32_t)k0 << 13) | ((uint32_t)nk << 20) | ((uint32_t)half << 27);
}
constexpr int MAX_LIST = 1536;
struct ItemTab { uint32_t v[MAX_LIST]; unsigned char slab[MAX_LIST]; };
#define LATE_MARGIN 60
#define TAIL_RB 15
#define QP_ROUND 8
#define O_R0 2
#define O_RS 4
#define N_PRE 1
constexpr void push_o(ItemTab& t, int& n, int g) {
    const int sp = spl(g);
    if (g == 15) {
        for (int k = 0; k < sp - 1; k++) for (int j = 0; j < 5; j++) { t.slab[n] = slab0(g) + k; t.v[n++] = mk_item(3, g, j, k * 96 / (sp - 1), (k + 1) * 96 / (sp - 1) - k * 96 / (sp - 1), 2); }
        return;
    }
    for (int k = 0; k < sp; k++) {
        const int a = k == 0 ? 0 : k * 106 / sp - 10, b = (k + 1) * 106 / sp - 10;
        for (int j = 0; j < 5; j++) { t.slab[n] = sp == 1 ? 255 : slab0(g) + k; t.v[n++] = mk_item(3, g, j, a, b - a, 2) | (k == 0 ? 1u << 29 : 0u); }
    }
}
constexpr void push_bp(ItemTab& t, int& n, int g) {
    for (int j = 0; j < 5; j++) { t.slab[n] = slab0(g) + spl(g) - 1; t.v[n++] = mk_item(3, g, j, 0, 0, 2) | 1u << 29; }
}
constexpr void push_f(ItemTab& t, int& n, int g) {
    if (spl(g) > 1) for (int j = 0; j < 5; j++) { t.slab[n] = slab0(g); t.v[n++] = mk_item(4, g, j, 0, spl(g), 2); }
}
constexpr ItemTab build_items() {
    ItemTab t{};
    int n = 0;
    for (int r = 0; r <= B_AHEAD; r++) for (int j = 0; j < 10; j++) t.v[n++] = mk_item(6, r, j, 0, 10, 2) | 1u << 29;
    for (int r = 0; r < 16; r++) t.v[n++] = mk_item(2, r, 0, 0, 0, 2);
    for (int r = 0; r < B_AHEAD; r++) for (int j = 0; j < 8; j++) t.v[n++] = mk_item(1, r, j, 0, 0, 2);
    for (int r = 0; r < 15; r++) {
        for (int g = 0; g < NFULL; g++) if (O_R0 + g * O_RS / 2 == r) push_o(t, n, g);
        if (r + B_AHEAD < 16) for (int j = 0; j < 8; j++) t.v[n++] = mk_item(1, r + B_AHEAD, j, 0, 0, 2);
        if (r + B_AHEAD + 1 < 16) for (int j = 0; j < 10; j++) t.v[n++] = mk_item(6, r + B_AHEAD + 1, j, 0, 10, 2) | 1u << 29;
        if (r == 14) push_bp(t, n, 15);
        for (int j = 0; j < 32; j++) t.v[n++] = mk_item(5, r, j, 0, 10, 2) | (r >= QPRE ? 1u << 29 : 0u);
        if (r >= QP_ROUND && QPRE + r - QP_ROUND < 16) for (int j = 0; j < 32; j++) t.v[n++] = mk_item(6, QPRE + r - QP_ROUND, j, 0, 10, 2);
    }
    for (int g = NFULL; g < NFULL + N_PRE; g++) push_o(t, n, g);
    if (15 >= QPRE) {
        for (int j = 0; j < 32; j++) t.v[n++] = mk_item(5, 15, j, 0, 10, 0) | 1u << 29;
        for (int j = 0; j < 32; j++) t.v[n++] = mk_item(5, 15, j, 0, 10, 1) | 1u << 29;
    } else {
        for (int j = 0; j < 32; j++) t.v[n++] = mk_item(5, 15, j, 0, 10, 2);
    }
    for (int g = NFULL + N_PRE; g < 16; g++) push_o(t, n, g);
    for (int g = NFULL; g < 16; g++) push_f(t, n, g);
    while (n < MAX_LIST) t.v[n++] = 7u;
    return t;
}
static_assert(O_R0 + (NFULL - 1) * O_RS / 2 < 15, "list");
constexpr int tail_start() {
    const ItemTab t = build_items();
    for (int i = 0; i < MAX_LIST; i++) if ((t.v[i] & 7u) == 5u && ((t.v[i] >> 3) & 15u) == TAIL_RB) return i;
    return MAX_LIST;
}
__device__ const ItemTab g_list = build_items();
constexpr int TAIL_START = tail_start();
#define MAX_ITEMS 1536
#define MAX_ITEMS_DEF
__device__ __forceinline__ Item unpack_item(uint32_t w, uint32_t slab) {
    Item it;
    it.slab = slab & 255;
    it.type = w & 7; it.mb = (w >> 3) & 15; it.nb = (w >> 7) & 63; it.k0 = (w >> 13) & 127; it.nk = (w >> 20) & 127; it.half = (w >> 27) & 3; it.bpart = (w >> 29) & 1;
    return it;
}
__device__ __forceinline__ void wait_cnt(const unsigned* c, unsigned want) {
    unsigned v; int n = 0;
#pragma unroll 1
    while (true) {
        asm volatile("ld.acquire.gpu.global.u32 %0, [%1];" : "=r"(v) : "l"(c) : "memory");
        if (v >= want) break;
        if (++n > (1 << 22)) { g_err = 5; break; }
        __nanosleep(200);
    }
}
__device__ __forceinline__ void wait_cnt3(const unsigned* c0, unsigned w0, const unsigned* c1, unsigned w1, const unsigned* c2, unsigned w2) {
    const int lane = threadIdx.x & 31;
    const unsigned* c = lane == 0 ? c0 : lane == 1 ? c1 : lane == 2 ? c2 : nullptr;
    const unsigned want = lane == 0 ? w0 : lane == 1 ? w1 : w2;
    int n = 0;
#pragma unroll 1
    while (true) {
        unsigned v = want;
        if (c) asm volatile("ld.acquire.gpu.global.u32 %0, [%1];" : "=r"(v) : "l"(c) : "memory");
        if (__all_sync(0xffffffffu, v >= want)) break;
        if (++n > (1 << 22)) { g_err = 5; break; }
        __nanosleep(100);
    }
    __syncwarp();
}
__device__ __forceinline__ void signal_cnt(unsigned* c) { asm volatile("fence.proxy.async;" ::: "memory"); asm volatile("red.release.gpu.global.add.u32 [%0], 1;" :: "l"(c) : "memory"); }

__device__ __forceinline__ void stage_tile_bf16(uint32_t stg, const float* acc, int lane, int w) {
    const uint32_t r = w * 16 + (lane & 7) + ((lane >> 3) & 1) * 8;
#pragma unroll
    for (int i = 0; i < 16; i += 2) {
        const uint32_t ch = (i & 7) + (lane >> 4);
        stsm4(stg + (i >> 3) * 8192 + r * 128 + ((ch ^ (r & 7)) << 4), pack_bf16(acc[4 * i], acc[4 * i + 1]), pack_bf16(acc[4 * i + 2], acc[4 * i + 3]),
              pack_bf16(acc[4 * i + 4], acc[4 * i + 5]), pack_bf16(acc[4 * i + 6], acc[4 * i + 7]));
    }
}

__device__ __forceinline__ void ldsm4_n(uint32_t& r0, uint32_t& r1, uint32_t& r2, uint32_t& r3, uint32_t a) {
    asm("ldmatrix.sync.aligned.m8n8.x4.shared.b16 {%0,%1,%2,%3}, [%4];" : "=r"(r0), "=r"(r1), "=r"(r2), "=r"(r3) : "r"(a));
}
__device__ __forceinline__ void ldsm4t_n(uint32_t& r0, uint32_t& r1, uint32_t& r2, uint32_t& r3, uint32_t a) {
    asm("ldmatrix.sync.aligned.m8n8.x4.trans.shared.b16 {%0,%1,%2,%3}, [%4];" : "=r"(r0), "=r"(r1), "=r"(r2), "=r"(r3) : "r"(a));
}
__device__ __forceinline__ void ldsm2_n(uint32_t& r0, uint32_t& r1, uint32_t a) {
    asm("ldmatrix.sync.aligned.m8n8.x2.shared.b16 {%0,%1}, [%2];" : "=r"(r0), "=r"(r1) : "r"(a));
}
__device__ __forceinline__ void ldsm2t_n(uint32_t& r0, uint32_t& r1, uint32_t a) {
    asm("ldmatrix.sync.aligned.m8n8.x2.trans.shared.b16 {%0,%1}, [%2];" : "=r"(r0), "=r"(r1) : "r"(a));
}
__device__ __forceinline__ uint32_t dep_on(uint32_t x, uint32_t d) { uint32_t r; asm volatile("{ .reg .u32 t; and.b32 t, %2, 0; add.u32 %0, %1, t; }" : "=r"(r) : "r"(x), "r"(d)); return r; }
template <int hf>
__device__ __forceinline__ void attnA_scores(uint32_t kv, const uint32_t (&qa)[48], int lane, uint32_t (&pa)[10]) {
    const int g = lane >> 2, t = lane & 3;
    float sc[5][4];
#pragma unroll
    for (int n = 0; n < 5; n++) { sc[n][0] = sc[n][1] = sc[n][2] = sc[n][3] = 0.f; }
    const uint32_t kb = kv + ((lane >> 3) & 1) * 640 + (lane >> 4) * 128 + (lane & 7) * 16;
#pragma unroll
    for (int ks = 0; ks < 12; ks++) {
        uint32_t b0, b1, b2, b3;
        const uint32_t a0 = qa[4 * ks], a1 = qa[4 * ks + 1], a2 = qa[4 * ks + 2], a3 = qa[4 * ks + 3];
        const uint32_t kk = kb + (ks >> 2) * 10240 + (ks & 3) * 1280;
        ldsm4t_n(b0, b1, b2, b3, kk);
        mma16816_n(sc[0], a0, a1, a2, a3, b0, b1); mma16816_n(sc[1], a0, a1, a2, a3, b2, b3);
        if (hf) { ldsm4t_n(b0, b1, b2, b3, kk + 256); mma16816_n(sc[2], a0, a1, a2, a3, b0, b1); mma16816_n(sc[3], a0, a1, a2, a3, b2, b3); }
        ldsm2t_n(b0, b1, kk + 512 - (lane >> 4) * 128);
        mma16816_n(sc[4], a0, a1, a2, a3, b0, b1);
    }
    const int lim = 16 * hf + g - 2 * t;
    float m0 = fmaxf(sc[4][0], sc[4][1]), m1 = fmaxf(sc[4][2], sc[4][3]);
#pragma unroll
    for (int n = 0; n < 4; n++) {
        if (8 * n > lim) sc[n][0] = -3.0e38f;
        if (8 * n + 1 > lim) sc[n][1] = -3.0e38f;
        if (8 * n > lim + 8) sc[n][2] = -3.0e38f;
        if (8 * n + 1 > lim + 8) sc[n][3] = -3.0e38f;
        m0 = fmaxf(m0, fmaxf(sc[n][0], sc[n][1])); m1 = fmaxf(m1, fmaxf(sc[n][2], sc[n][3]));
    }
    m0 = fmaxf(m0, __shfl_xor_sync(0xffffffffu, m0, 1)); m1 = fmaxf(m1, __shfl_xor_sync(0xffffffffu, m1, 1));
    m0 = fmaxf(m0, __shfl_xor_sync(0xffffffffu, m0, 2)); m1 = fmaxf(m1, __shfl_xor_sync(0xffffffffu, m1, 2));
    m0 *= SCALE_A; m1 *= SCALE_A;
    float s0 = 0.f, s1 = 0.f;
#pragma unroll
    for (int n = 0; n < 5; n++) {
        sc[n][0] = ex2(fmaf(fmaxf(sc[n][0], -1.0e30f), SCALE_A, -m0)); sc[n][1] = ex2(fmaf(fmaxf(sc[n][1], -1.0e30f), SCALE_A, -m0));
        sc[n][2] = ex2(fmaf(fmaxf(sc[n][2], -1.0e30f), SCALE_A, -m1)); sc[n][3] = ex2(fmaf(fmaxf(sc[n][3], -1.0e30f), SCALE_A, -m1));
        s0 += sc[n][0] + sc[n][1]; s1 += sc[n][2] + sc[n][3];
    }
    s0 += __shfl_xor_sync(0xffffffffu, s0, 1); s1 += __shfl_xor_sync(0xffffffffu, s1, 1);
    s0 += __shfl_xor_sync(0xffffffffu, s0, 2); s1 += __shfl_xor_sync(0xffffffffu, s1, 2);
    const float i0 = rcp(s0), i1 = rcp(s1);
#pragma unroll
    for (int n = 0; n < 5; n++) { pa[2 * n] = pack_bf16(sc[n][0] * i0, sc[n][1] * i0); pa[2 * n + 1] = pack_bf16(sc[n][2] * i1, sc[n][3] * i1); }
}
template <int hf>
__device__ __forceinline__ void attnA_pv(uint32_t kv, uint32_t stg, int w, int lane, const uint32_t (&pa)[10]) {
    const uint32_t vb = kv + 5120 + (lane >> 3) * 128 + (lane & 7) * 16;
    const uint32_t orow = w * 16 + (lane & 7) + ((lane >> 3) & 1) * 8;
    uint32_t ob[48];
#pragma unroll
    for (int sl = 0; sl < 3; sl++) {
#pragma unroll
        for (int dg = 0; dg < 8; dg += 2) {
            float o[2][4];
            uint32_t m0, m1;
            ldsm2_n(m0, m1, kv + 5120 + sl * 10240 + dg * 640 + 512 + ((lane >> 3) & 1) * 640 + (lane & 7) * 16);
#pragma unroll
            for (int j = 0; j < 2; j++) {
                uint32_t b0, b1, b2, b3;
                ldsm4_n(b0, b1, b2, b3, vb + sl * 10240 + (dg + j) * 640);
                o[j][0] = o[j][1] = o[j][2] = o[j][3] = 0.f;
                mma16816_n(o[j], pa[0], pa[1], pa[2], pa[3], b0, b1);
                if (hf) mma16816_n(o[j], pa[4], pa[5], pa[6], pa[7], b2, b3);
                mma1688_n(o[j], pa[8], pa[9], j ? m1 : m0);
            }
            const int q = (sl * 4 + (dg >> 1)) * 4;
            ob[q] = pack_bf16(o[0][0], o[0][1]); ob[q + 1] = pack_bf16(o[0][2], o[0][3]); ob[q + 2] = pack_bf16(o[1][0], o[1][1]); ob[q + 3] = pack_bf16(o[1][2], o[1][3]);
        }
    }
#pragma unroll
    for (int sl = 0; sl < 3; sl++)
#pragma unroll
        for (int dg = 0; dg < 8; dg += 2) {
            const int q = (sl * 4 + (dg >> 1)) * 4;
            stsm4(stg + sl * 8192 + orow * 128 + (((dg + (lane >> 4)) ^ (lane & 7)) << 4), ob[q], ob[q + 1], ob[q + 2], ob[q + 3]);
        }
}

__global__ void __launch_bounds__(384, 1)
aux_kernel(const __grid_constant__ CUtensorMap tm_x, const __grid_constant__ CUtensorMap tm_wqkv, const __grid_constant__ CUtensorMap tm_oB,
           const __grid_constant__ CUtensorMap tm_woB, const __grid_constant__ CUtensorMap tm_oA, const __grid_constant__ CUtensorMap tm_wo,
           const __grid_constant__ CUtensorMap ts_qkv, const __grid_constant__ CUtensorMap tm_oB64, const __grid_constant__ CUtensorMap ts_out,
           const __grid_constant__ CUtensorMap ts_acc, const __grid_constant__ CUtensorMap tm_oA64, const __grid_constant__ CUtensorMap tm_wq,
           const __grid_constant__ CUtensorMap tm_x64, const __grid_constant__ CUtensorMap tm_qkvB, const __grid_constant__ CUtensorMap ts_oB, const __grid_constant__ CUtensorMap tm_qp, const __grid_constant__ CUtensorMap ts_part,
           const bf16* __restrict__ x, const bf16* __restrict__ gate_w) {
    extern __shared__ __align__(1024) char smem_raw[];
    const uint32_t sb = smem_u32(smem_raw);
    const uint32_t bar = sb + G_OUT + 2 * STG_BYTES;
    if (threadIdx.x == 0) {
        for (int i = 0; i < 8; i++) { mbar_init(bar + 8 * i, 1); mbar_init(bar + 64 + 8 * i, 8); }
        for (int i = 0; i < 2; i++) {
            mbar_init(bar + 128 + 8 * i, 1); mbar_init(bar + 144 + 8 * i, 2);
            mbar_init(bar + 224 + 8 * i, 128); mbar_init(bar + 240 + 8 * i, 1);
        }
        asm volatile("fence.mbarrier_init.release.cluster;" ::: "memory");
    }
    __syncthreads();
    const int wid = __shfl_sync(0xffffffffu, (int)(threadIdx.x >> 5), 0), wg = wid >> 2;
    if (wg == 2) {
        asm volatile("setmaxnreg.dec.sync.aligned.u32 40;");
        const bool lead = elect_one();
        if (wid == 8) {
            const uint64_t pol = pol_stream();
            uint32_t seq = 0, tail = 0, cur = 0, used = 0;
            uint64_t alloc = 0;
#define RING_ACQ(size) \
                const uint32_t pad_ = cur + (size) > RING_CAP ? RING_CAP - cur : 0u; \
                if (cur + (size) > RING_CAP) cur = 0; \
                while (used + pad_ + (size) > RING_CAP || seq - tail >= 8u) { \
                    mbar_wait(bar + 64 + 8 * (tail & 7u), (tail >> 3) & 1u); \
                    used -= (uint32_t)((alloc >> (8 * (tail & 7u))) & 255u) << 10; tail++; } \
                alloc = (alloc & ~(255ull << (8 * (seq & 7u)))) | ((uint64_t)((pad_ + (size)) >> 10) << (8 * (seq & 7u))); \
                used += pad_ + (size); \
                const uint32_t d = sb + cur, fb = bar + 8 * (seq & 7u)
#define RING_ADV(size) { cur += (size); seq++; }
            uint32_t nidx = 0;
#define REQ_NOW() { if (lead) nidx = atomicAdd(&g_ctl.next, 1u); }
#define REQ_NEXT() { if (!late) REQ_NOW(); }
            bool late = false;
            REQ_NOW();
            for (int n = 0;; n++) {
                if (late) {
                    while (tail != seq) { mbar_wait(bar + 64 + 8 * (tail & 7u), (tail >> 3) & 1u); used -= (uint32_t)((alloc >> (8 * (tail & 7u))) & 255u) << 10; tail++; }
                    REQ_NOW();
                }
                const uint32_t gidx = __reduce_max_sync(0xffffffffu, nidx);
                late = gidx + LATE_MARGIN >= (uint32_t)TAIL_START;
                nidx = 0;
                const uint32_t nw = __shfl_sync(0xffffffffu, gidx < MAX_LIST ? g_list.v[gidx] : 7u, 0);
                const uint32_t nsl = __shfl_sync(0xffffffffu, gidx < MAX_LIST ? (uint32_t)g_list.slab[gidx] : 0u, 0) | (gidx << 8);
                const Item it = unpack_item(nw, nsl);
                if (n >= 2) mbar_wait(bar + 144 + 8 * (n & 1), ((n >> 1) - 1) & 1);
                if (lead) { sts64(bar + 160 + 8 * (n & 1), nw, nsl); mbar_arrive(bar + 128 + 8 * (n & 1)); }
                if (it.type == 7) break;
                if (it.type == 2) { REQ_NEXT(); continue; }
                if (it.type == 1) {
                    wait_cnt3(&g_ctl.b1[it.mb], 20, it.mb > 0 && it.nb < 4 ? &g_ctl.b1[it.mb - 1] : nullptr, 20, nullptr, 0);
                    asm volatile("fence.proxy.async;" ::: "memory");
                    for (int p = 0; p < 3; p++) {
                        RING_ACQ(SZ_B);
                        if (lead) { mbar_expect(fb, 80 * 336); tma2d_s(d, &tm_qkvB, p * 640 + (it.nb & 3) * 160, it.mb * 128 + (it.nb >> 2) * 64 - 14, fb, pol); }
                        RING_ADV(SZ_B);
                    }
                    REQ_NEXT();
                    continue;
                }
                if (it.type == 5 || it.type == 6) {
                    const CUtensorMap* ta = it.half == 2 ? &tm_x : &tm_x64;
                    const int arow = it.mb * 128 + (it.half == 1 ? 64 : 0), bcol = it.nb * 192;
                    const uint32_t aoff = it.half == 1 ? 8192 : 0, bytes = it.half == 2 ? 40960 : 32768;
                    const CUtensorMap* tbq = it.type == 6 && it.bpart ? &tm_wqkv : &tm_wq;
                    if (it.type == 5 && it.bpart) {
                        wait_cnt3(&g_ctl.qp[it.mb - QPRE], 64, it.half != 1 ? &g_ctl.seg[it.mb * 2] : nullptr, 2 * NCTA, it.half != 0 ? &g_ctl.seg[it.mb * 2 + 1] : nullptr, 2 * NCTA);
                        asm volatile("fence.proxy.async;" ::: "memory");
                        RING_ACQ(SZ_QP);
                        if (lead) {
                            mbar_expect(fb, it.half == 2 ? 49152 : 24576);
                            for (int h = (it.half == 1); h <= (it.half != 0); h++)
#pragma unroll
                                for (int c = 0; c < 3; c++) tma2d(d + h * 24576 + c * 8192, &tm_qp, bcol + c * 64, (it.mb - QPRE) * 128 + h * 64, fb);
                        }
                        RING_ADV(SZ_QP);
                    } else
                    for (int k = 0; k < 640; k += 64) {
                        if (it.type == 6 && k == 192) REQ_NEXT();
                        RING_ACQ(SZ_Q);
                        if (lead) {
                            mbar_expect(fb, bytes);
                            tma2d(d + aoff, ta, k, arow, fb);
#pragma unroll
                            for (int c = 0; c < 3; c++) tma2d(d + 16384 + c * 8192, tbq, bcol + c * 64, k, fb);
                        }
                        RING_ADV(SZ_Q);
                    }
                    if (it.type == 6) continue;
                    if (!it.bpart) {
                        wait_cnt3(it.half != 1 ? &g_ctl.seg[it.mb * 2] : nullptr, 2 * NCTA, it.half != 0 ? &g_ctl.seg[it.mb * 2 + 1] : nullptr, 2 * NCTA, nullptr, 0);
                        asm volatile("fence.proxy.async;" ::: "memory");
                    }
                    REQ_NEXT();
                    for (int j = (it.half == 1 ? 2 : 0); j < (it.half == 0 ? 2 : 4); j++) {
                        const char* kv = g_kv + (size_t)((it.mb * 4 + j) * NCTA + it.nb * 3) * 10240;
                        RING_ACQ(SZ_KV);
                        if (lead) { mbar_expect(fb, 30720); bulk_g2s_s(d, kv, 30720, fb, pol); }
                        RING_ADV(SZ_KV);
                    }
                    continue;
                }
                const int arow = it.mb * 128 + (it.half == 1 ? 64 : 0), bcol = it.nb * 128;
                const uint32_t aoff = it.half == 1 ? 8192 : 0, bytes = it.half == 2 ? 32768 : 24576;
                if (it.type == 4) {
                    REQ_NEXT();
                    wait_cnt3(it.half != 1 ? &g_ctl.fin[it.mb * 10 + it.nb] : nullptr, it.nk, it.half != 0 ? &g_ctl.fin[it.mb * 10 + 5 + it.nb] : nullptr, it.nk, nullptr, 0);
                    asm volatile("fence.proxy.async;" ::: "memory");
                    const int s0 = it.slab;
                    for (int p = 0; p < it.nk; p++) {
                        RING_ACQ(SZ_G);
                        if (lead) {
                            mbar_expect(fb, 32768);
                            tma2d_s(d, &ts_acc, bcol, (s0 + p) * 128, fb, pol);
                            tma2d_s(d + 16384, &ts_acc, bcol + 64, (s0 + p) * 128, fb, pol);
                        }
                        RING_ADV(SZ_G);
                    }
                    continue;
                }
                if (it.type == 3) {
                    wait_cnt3(&g_ctl.at[it.mb], 17, it.nk && it.half != 1 ? &g_ctl.ata[it.mb * 2] : nullptr, 32, it.nk && it.half != 0 ? &g_ctl.ata[it.mb * 2 + 1] : nullptr, 32);
                    asm volatile("fence.proxy.async;" ::: "memory");
                }
                const int kend = (it.k0 + it.nk) * 64, kreq = kend - 64 * (it.nk < REQ_AHEAD ? it.nk : REQ_AHEAD);
                if (it.type == 0 || it.bpart) {
                    if (it.type == 3 && it.nk == 0) REQ_NEXT();
                    const CUtensorMap* ta = it.type == 0 ? &tm_x : it.half == 2 ? &tm_oB : &tm_oB64;
                    const CUtensorMap* tb = it.type == 0 ? &tm_wqkv : &tm_woB;
                    for (int k = 0; k < 640; k += 64) {
                        if (it.type == 0 && k == kreq) REQ_NEXT();
                        RING_ACQ(SZ_G);
                        if (lead) {
                            mbar_expect(fb, bytes);
                            tma2d(d + aoff, ta, k, arow, fb);
                            tma2d(d + 16384, tb, bcol, k, fb);
                            tma2d(d + 24576, tb, bcol + 64, k, fb);
                        }
                        RING_ADV(SZ_G);
                    }
                    if (it.type == 0) continue;
                }
                const CUtensorMap* ta = it.half == 2 ? &tm_oA : &tm_oA64;
                for (int k = it.k0 * 64; k < kend; k += 64) {
                    if (k == kreq) REQ_NEXT();
                    RING_ACQ(SZ_G);
                    if (lead) {
                        mbar_expect(fb, bytes);
                        tma2d_s(d + aoff, ta, k, arow, fb, pol);
                        tma2d(d + 16384, &tm_wo, bcol, k, fb);
                        tma2d(d + 24576, &tm_wo, bcol + 64, k, fb);
                    }
                    RING_ADV(SZ_G);
                }
            }
#undef RING_ACQ
#undef RING_ADV
#undef REQ_NEXT
#undef REQ_NOW
        } else if (wid < 11) {
            const int sw = wid - 9;
            const uint32_t stg = sb + G_OUT + sw * STG_BYTES;
            const uint64_t spol = pol_stream();
            for (uint32_t ph = 0;; ph ^= 1) {
                mbar_wait(bar + 224 + 8 * sw, ph);
                const uint4 mv = lds128(bar + 256 + 16 * sw);
                const int kind = __shfl_sync(0xffffffffu, (int)mv.x, 0), col = __shfl_sync(0xffffffffu, (int)mv.y, 0), row = __shfl_sync(0xffffffffu, (int)mv.z, 0);
                const int cnt = __shfl_sync(0xffffffffu, (int)mv.w, 0);
                if (kind < 0) break;
                const CUtensorMap* tm = kind == 0 || kind == 7 ? &ts_qkv : kind == 2 ? &ts_out : kind == 5 ? &ts_part : kind == 3 ? &tm_oA64 : kind == 6 ? &tm_qp : &ts_oB;
                if (lead) {
                    {
                        if (kind == 2) {
                            asm volatile("cp.async.bulk.tensor.2d.global.shared::cta.bulk_group.L2::cache_hint [%0, {%2, %3}], [%1], %4;" :: "l"(tm), "r"(stg), "r"(col), "r"(row), "l"(spol) : "memory");
                            asm volatile("cp.async.bulk.tensor.2d.global.shared::cta.bulk_group.L2::cache_hint [%0, {%2, %3}], [%1], %4;" :: "l"(tm), "r"(stg + 8192), "r"(col + 64), "r"(row), "l"(spol) : "memory");
                        } else
                        asm volatile("cp.async.bulk.tensor.2d.global.shared::cta.bulk_group [%0, {%2, %3}], [%1];" :: "l"(tm), "r"(stg), "r"(col), "r"(row) : "memory");
                        if (kind != 4 && !((EVF & 8) && kind == 2))
                            asm volatile("cp.async.bulk.tensor.2d.global.shared::cta.bulk_group [%0, {%2, %3}], [%1];" :: "l"(tm), "r"(stg + 8192), "r"(col + 64), "r"(row) : "memory");
                        if (kind == 3 || kind == 6 || kind == 7)
                            asm volatile("cp.async.bulk.tensor.2d.global.shared::cta.bulk_group [%0, {%2, %3}], [%1];" :: "l"(tm), "r"(stg + 16384), "r"(col + 128), "r"(row) : "memory");
                    }
                    asm volatile("cp.async.bulk.commit_group;" ::: "memory");
                    asm volatile("cp.async.bulk.wait_group.read 0;" ::: "memory");
                    mbar_arrive(bar + 240 + 8 * sw);
                    asm volatile("cp.async.bulk.wait_group 0;" ::: "memory");
                    if (cnt >= 0) signal_cnt((unsigned*)&g_ctl + cnt);
                }
                __syncwarp();
            }
        }
        asm volatile("griddepcontrol.wait;" ::: "memory");
    } else {
        asm volatile("setmaxnreg.inc.sync.aligned.u32 232;");
        const int lane = threadIdx.x & 31, w = wid & 3, g = lane >> 2, t = lane & 3;
        const uint32_t stg = sb + G_OUT + wg * STG_BYTES;
        uint32_t seq_o = 0, cur_o = 0;
        uint32_t n_st = 0, n_free = 0;
#define RING_WAIT(size) { if (cur + (size) > RING_CAP) cur = 0; mbar_wait(bar + 8 * (seq & 7u), (seq >> 3) & 1u); }
#define RING_ADV(size) { cur += (size); seq++; }
#define RING_FREE(sq) mbar_arrive(bar + 64 + 8 * ((sq) & 7u))
#define RING_SAVE() { seq_o = seq; cur_o = cur; }
#define STG_ACQ() if (n_free != n_st) { mbar_wait(bar + 240 + 8 * wg, n_free & 1); n_free++; }
#define STG_POST(kind, col, row, cnt) { if ((threadIdx.x & 127) == 0) sts128(bar + 256 + 16 * wg, make_uint4((uint32_t)(kind), (uint32_t)(col), (uint32_t)(row), (uint32_t)(cnt))); \
                                        fence_async_smem(); mbar_arrive(bar + 224 + 8 * wg); n_st++; }
#define GEMM_STAGE(FN, acc, FIRST, size) { \
                    RING_WAIT(size); \
                    const uint32_t d = sb + cur; \
                    const uint64_t da = make_desc(d + wg * 8192, 16, 1024, 1), db = make_desc(d + 16384, 8192, 1024, 1); \
                    wg_fence(); \
                    if (FIRST) FN##_first(acc, da, db); else FN(acc, da, db, 1); \
                    _Pragma("unroll") for (int kk = 1; kk < 4; kk++) FN(acc, da + kk * 2, db + kk * 128, 1); \
                    wg_commit(); }
#define GEMM_LOOP(FN, acc, nks, size) { \
                GEMM_STAGE(FN, acc, true, size) \
                RING_ADV(size); \
                for (int k = 1; k < (nks); k++) { \
                    GEMM_STAGE(FN, acc, false, size) \
                    wg_wait<1>(); \
                    if (lane == 0) RING_FREE(seq - 1); \
                    RING_ADV(size); \
                } \
                wg_wait<0>(); \
                if (lane == 0) RING_FREE(seq - 1); }
#define GEMM128(acc, nks) GEMM_LOOP(wgmma_ss_n128_tb, acc, nks, SZ_G)
        for (int n = 0;; n++) {
            mbar_wait(bar + 128 + 8 * (n & 1), (n >> 1) & 1);
            const uint32_t iw = __shfl_sync(0xffffffffu, lds32(bar + 160 + 8 * (n & 1)), 0);
            const uint32_t isl = __shfl_sync(0xffffffffu, lds32(bar + 164 + 8 * (n & 1)), 0);
            bar_sync(1 + wg, 128);
            if ((threadIdx.x & 127) == 0) mbar_arrive(bar + 144 + 8 * (n & 1));
            const Item it = unpack_item(iw, isl);
            if (it.type == 7) { STG_ACQ(); STG_POST(-1, 0, 0, -1); break; }
            uint32_t seq = (uint32_t)opaque((int)seq_o), cur = (uint32_t)opaque((int)cur_o);
            if (it.type == 2) {
                gate8(it.mb * 128 + wid * 16, lane, x, gate_w);
                gate8(it.mb * 128 + wid * 16 + 8, lane, x, gate_w);
                __threadfence();
                bar_sync(3, 256);
                if (threadIdx.x == 0) signal_cnt(&g_ctl.at[it.mb]);
                continue;
            }
            if (it.type == 1) {
                const int t0 = it.mb * 128 + (it.nb >> 2) * 64;
                RING_WAIT(SZ_B);
                const uint32_t s0 = cur;
                RING_ADV(SZ_B);
                RING_WAIT(SZ_B);
                const uint32_t s1 = cur;
                RING_ADV(SZ_B);
                uint32_t pa[4][8];
                const uint32_t dq = (uint32_t)opaque((int)(sb + s0 + wid * 40)), dk = (uint32_t)opaque((int)(sb + s1 + wid * 40));
                if (t0 == 0) attnB_scores<true>(dq, dk, 0, t0, lane, pa[0]); else attnB_scores<false>(dq, dk, 0, t0, lane, pa[0]);
#pragma unroll
                for (int i = 1; i < 4; i++) attnB_scores<false>(dq, dk, i, t0, lane, pa[i]);
                asm volatile("" :: "r"(pa[0][0]), "r"(pa[1][0]), "r"(pa[2][0]), "r"(pa[3][0]) : "memory");
                __syncwarp();
                if (lane == 0) { RING_FREE(seq - 2); RING_FREE(seq - 1); }
                STG_ACQ();
                bar_sync(3, 256);
                RING_WAIT(SZ_B);
                const uint32_t dv = (uint32_t)opaque((int)(sb + cur + wid * 40));
                uint32_t ob[4][6];
#pragma unroll
                for (int i = 0; i < 4; i++) attnB_pv(dv, i, lane, pa[i], ob[i]);
#pragma unroll
                for (int i = 0; i < 4; i++) {
                    const uint32_t out = sb + G_OUT + (i >> 1) * STG_BYTES + (i & 1) * 16 * 320 + wid * 40 + g * 320 + t * 4;
#pragma unroll
                    for (int n = 0; n < 3; n++)
                        if (n < 2 || t < 2) { sts32(out + n * 16, ob[i][2 * n]); sts32(out + 8 * 320 + n * 16, ob[i][2 * n + 1]); }
                }
                __syncwarp();
                if (lane == 0) RING_FREE(seq);
                RING_ADV(SZ_B);
                RING_SAVE();
                fence_async_smem();
                bar_sync(3, 256);
                STG_POST(4, (it.nb & 3) * 160, t0 + wg * 32, (int)(offsetof(AuxCtl, at) / 4) + it.mb);
                continue;
            }
            const bool active = it.half == 2 || it.half == wg;
            if (!active) {
                const int nq = it.bpart ? 1 : 10;
                const int ns = it.type == 5 ? nq + 2 : it.nk + (it.bpart ? 10 : 0);
                for (int k = 0; k < ns; k++) {
                    const uint32_t sz = it.type == 5 ? (k < nq ? (it.bpart ? SZ_QP : SZ_Q) : SZ_KV) : SZ_G;
                    RING_WAIT(sz);
                    if (lane == 0) RING_FREE(seq);
                    RING_ADV(sz);
                }
                RING_SAVE();
                continue;
            }
            if (it.type == 6) {
                float acc[96];
                GEMM_LOOP(wgmma_ss_n192_tb, acc, 10, SZ_Q)
                RING_SAVE();
                STG_ACQ();
                const uint32_t r = w * 16 + (lane & 7) + ((lane >> 3) & 1) * 8;
#pragma unroll
                for (int i = 0; i < 24; i += 2) {
                    const uint32_t ch = (i & 7) + (lane >> 4);
                    stsm4(stg + (i >> 3) * 8192 + r * 128 + ((ch ^ (r & 7)) << 4), pack_bf16(acc[4 * i], acc[4 * i + 1]), pack_bf16(acc[4 * i + 2], acc[4 * i + 3]),
                          pack_bf16(acc[4 * i + 4], acc[4 * i + 5]), pack_bf16(acc[4 * i + 6], acc[4 * i + 7]));
                }
                if (it.bpart) STG_POST(7, it.nb * 192, it.mb * 128 + wg * 64, (int)(offsetof(AuxCtl, b1) / 4) + it.mb)
                else STG_POST(6, it.nb * 192, (it.mb - QPRE) * 128 + wg * 64, (int)(offsetof(AuxCtl, qp) / 4) + it.mb - QPRE)
                continue;
            }
            if (it.type == 5) {
                uint32_t qa[48];
                if (it.bpart) {
                    RING_WAIT(SZ_QP);
                    const uint32_t r = w * 16 + (lane & 7) + ((lane >> 3) & 1) * 8, qs = sb + cur + wg * 24576 + r * 128;
#pragma unroll
                    for (int ks = 0; ks < 12; ks++)
                        ldsm4(qa[4 * ks], qa[4 * ks + 1], qa[4 * ks + 2], qa[4 * ks + 3], qs + (ks >> 2) * 8192 + (((2 * (ks & 3) + (lane >> 4)) ^ (r & 7)) << 4));
                    asm volatile("" :: "r"(qa[0]), "r"(qa[47]) : "memory");
                    __syncwarp();
                    if (lane == 0) RING_FREE(seq);
                    RING_ADV(SZ_QP);
                } else {
                    float acc[96];
                    GEMM_LOOP(wgmma_ss_n192_tb, acc, 10, SZ_Q)
#pragma unroll
                    for (int i = 0; i < 48; i++) qa[i] = pack_bf16(acc[2 * i], acc[2 * i + 1]);
                }
                STG_ACQ();
                const int own = 2 * wg + (w >> 1);
                for (int j = (it.half == 1 ? 2 : 0); j < (it.half == 0 ? 2 : 4); j++) {
                    RING_WAIT(SZ_KV);
                    if (j == own) {
                        uint32_t pa[10];
                        const uint32_t kv = (uint32_t)opaque((int)(sb + cur));
                        if (w & 1) { attnA_scores<1>(kv, qa, lane, pa); attnA_pv<1>(dep_on(kv, pa[0]), stg, w, lane, pa); }
                        else { attnA_scores<0>(kv, qa, lane, pa); attnA_pv<0>(dep_on(kv, pa[0]), stg, w, lane, pa); }
                    }
                    __syncwarp();
                    if (lane == 0) RING_FREE(seq);
                    RING_ADV(SZ_KV);
                }
                RING_SAVE();
                STG_POST(3, it.nb * 192, it.mb * 128 + wg * 64, (int)(offsetof(AuxCtl, ata) / 4) + it.mb * 2 + wg);
                continue;
            }
            const uint32_t rr = w * 16 + g;
            if (it.type == 4) {
                float acc[64];
#pragma unroll
                for (int i = 0; i < 64; i++) acc[i] = 0.f;
                const uint32_t r = wg * 64 + w * 16 + (lane & 7) + ((lane >> 3) & 1) * 8;
                for (int p = 0; p < it.nk; p++) {
                    RING_WAIT(SZ_G);
                    const uint32_t base = sb + cur + r * 128;
#pragma unroll
                    for (int i = 0; i < 16; i += 2) {
                        uint32_t u0, u1, u2, u3;
                        ldsm4(u0, u1, u2, u3, base + (i >> 3) * 16384 + ((((i & 7) + (lane >> 4)) ^ (r & 7)) << 4));
                        acc[4 * i] += bf_lo(u0); acc[4 * i + 1] += bf_hi(u0); acc[4 * i + 2] += bf_lo(u1); acc[4 * i + 3] += bf_hi(u1);
                        acc[4 * i + 4] += bf_lo(u2); acc[4 * i + 5] += bf_hi(u2); acc[4 * i + 6] += bf_lo(u3); acc[4 * i + 7] += bf_hi(u3);
                    }
                    __syncwarp();
                    if (lane == 0) RING_FREE(seq);
                    RING_ADV(SZ_G);
                }
                RING_SAVE();
                STG_ACQ();
                stage_tile_bf16(stg, acc, lane, w);
                STG_POST(2, it.nb * 128, it.mb * 128 + wg * 64, -1);
                continue;
            }
            if (it.type == 0) {
                float acc[64];
                GEMM128(acc, 10)
                RING_SAVE();
                STG_ACQ();
                stage_tile_bf16(stg, acc, lane, w);
                STG_POST(0, it.nb * 128, it.mb * 128 + wg * 64, (int)(offsetof(AuxCtl, b1) / 4) + it.mb);
                continue;
            }
            uint32_t bb[32];
            if (it.bpart) {
                float accb[64];
                GEMM128(accb, 10)
#pragma unroll
                for (int i = 0; i < 32; i++) bb[i] = pack_bf16(accb[2 * i], accb[2 * i + 1]);
            } else {
#pragma unroll
                for (int i = 0; i < 32; i++) bb[i] = 0u;
            }
            float acc[64];
            if (it.nk) { GEMM128(acc, it.nk) }
            else {
#pragma unroll
                for (int i = 0; i < 64; i++) acc[i] = 0.f;
            }
            RING_SAVE();
            {
                const int r0 = it.mb * 128 + wg * 64 + rr;
                wait_cnt(&g_ctl.at[it.mb], 17);
                float g0, g1;
                asm volatile("ld.global.f32 %0, [%1];" : "=f"(g0) : "l"(g_gate + r0) : "memory");
                asm volatile("ld.global.f32 %0, [%1];" : "=f"(g1) : "l"(g_gate + r0 + 8) : "memory");
#pragma unroll
                for (int i = 0; i < 16; i++) {
                    acc[4 * i] = g0 * acc[4 * i] + (1.f - g0) * bf_lo(bb[2 * i]); acc[4 * i + 1] = g0 * acc[4 * i + 1] + (1.f - g0) * bf_hi(bb[2 * i]);
                    acc[4 * i + 2] = g1 * acc[4 * i + 2] + (1.f - g1) * bf_lo(bb[2 * i + 1]); acc[4 * i + 3] = g1 * acc[4 * i + 3] + (1.f - g1) * bf_hi(bb[2 * i + 1]);
                }
            }
            STG_ACQ();
            stage_tile_bf16(stg, acc, lane, w);
            if (it.slab == 255) STG_POST(2, it.nb * 128, it.mb * 128 + wg * 64, -1)
            else STG_POST(5, it.nb * 128, it.slab * 128 + wg * 64, (int)(offsetof(AuxCtl, fin) / 4) + (it.mb * 2 + wg) * 5 + it.nb)
        }
#undef GEMM128
#undef GEMM_LOOP
#undef GEMM_STAGE
#undef RING_WAIT
#undef RING_ADV
#undef RING_FREE
#undef RING_SAVE
#undef STG_ACQ
#undef STG_POST
        asm volatile("griddepcontrol.wait;" ::: "memory");
    }
}

typedef CUresult (*EncodeFn)(CUtensorMap*, CUtensorMapDataType, cuuint32_t, void*, const cuuint64_t*, const cuuint64_t*,
                             const cuuint32_t*, const cuuint32_t*, CUtensorMapInterleave, CUtensorMapSwizzle,
                             CUtensorMapL2promotion, CUtensorMapFloatOOBfill);

static CUtensorMap make_map(EncodeFn fn, const void* ptr, uint64_t cols, uint64_t rows, uint32_t bc, uint32_t br, bool f32 = false, bool swz = true) {
    CUtensorMap m;
    cuuint64_t dims[2] = {cols, rows};
    cuuint64_t strides[1] = {cols * (f32 ? 4 : 2)};
    cuuint32_t box[2] = {bc, br};
    cuuint32_t es[2] = {1, 1};
    fn(&m, f32 ? CU_TENSOR_MAP_DATA_TYPE_FLOAT32 : CU_TENSOR_MAP_DATA_TYPE_BFLOAT16, 2, (void*)ptr, dims, strides, box, es, CU_TENSOR_MAP_INTERLEAVE_NONE,
       swz ? CU_TENSOR_MAP_SWIZZLE_128B : CU_TENSOR_MAP_SWIZZLE_NONE, CU_TENSOR_MAP_L2_PROMOTION_L2_128B, CU_TENSOR_MAP_FLOAT_OOB_FILL_NONE);
    return m;
}

extern "C" void kernel_launch(void* const* d_in, const int* in_sizes, int n_in, void* d_out, int out_size) {
    const bf16* x = (const bf16*)d_in[0];
    const bf16* mem0 = (const bf16*)d_in[1];
    const bf16* Wq = (const bf16*)d_in[2];
    const bf16* Wk = (const bf16*)d_in[3];
    const bf16* Wv = (const bf16*)d_in[4];
    const bf16* Wo = (const bf16*)d_in[5];
    const bf16* wqkv = (const bf16*)d_in[8];
    const bf16* wo = (const bf16*)d_in[9];
    const bf16* gate_w = (const bf16*)d_in[10];
    bf16* out = (bf16*)d_out;

    static EncodeFn fn = nullptr;
    static int n_aux = 36;
    static void *p_acc, *p_oA, *p_qkvB, *p_oB, *p_Qp;
    if (!fn) {
        cudaDriverEntryPointQueryResult qr;
        void* f = nullptr;
        cudaGetDriverEntryPoint("cuTensorMapEncodeTiled", &f, cudaEnableDefault, &qr);
        fn = (EncodeFn)f;
        cudaGetSymbolAddress(&p_acc, g_part); cudaGetSymbolAddress(&p_oA, g_oA); cudaGetSymbolAddress(&p_qkvB, g_qkvB); cudaGetSymbolAddress(&p_oB, g_oB); cudaGetSymbolAddress(&p_Qp, g_Qp);
        int sms = 132;
        cudaDeviceGetAttribute(&sms, cudaDevAttrMultiProcessorCount, 0);
        n_aux = sms;
        cudaFuncSetAttribute(rec_kernel, cudaFuncAttributeMaxDynamicSharedMemorySize, REC_SMEM_L);
        cudaFuncSetAttribute(aux_kernel, cudaFuncAttributeMaxDynamicSharedMemorySize, GEMM_SMEM);
    }
    CUtensorMap tm_x32;
    {
        cuuint64_t dims[3] = {64, S_LEN, 10}, strides[2] = {DM * 2, 128};
        cuuint32_t box[3] = {64, 32, 5}, es[3] = {1, 1, 1};
        fn(&tm_x32, CU_TENSOR_MAP_DATA_TYPE_BFLOAT16, 3, (void*)x, dims, strides, box, es, CU_TENSOR_MAP_INTERLEAVE_NONE, CU_TENSOR_MAP_SWIZZLE_128B,
           CU_TENSOR_MAP_L2_PROMOTION_L2_128B, CU_TENSOR_MAP_FLOAT_OOB_FILL_NONE);
    }
    const CUtensorMap tm_wq = make_map(fn, Wq, HD, DM, 64, 128);
    const CUtensorMap tm_wk = make_map(fn, Wk, HD, DM, 64, 128);
    const CUtensorMap tm_wv = make_map(fn, Wv, HD, DM, 64, 128);
    const CUtensorMap tm_wo = make_map(fn, Wo, DM, HD, 64, 64);
    const CUtensorMap tm_x128 = make_map(fn, x, DM, S_LEN, 64, 128);
    const CUtensorMap tm_wqkv = make_map(fn, wqkv, 3 * DM, DM, 64, 64);
    const CUtensorMap tm_oB = make_map(fn, p_oB, DM, S_LEN, 64, 128);
    const CUtensorMap tm_woB = make_map(fn, wo, DM, DM, 64, 64);
    const CUtensorMap tm_oA = make_map(fn, p_oA, HD, S_LEN, 64, 128);

    rec_kernel<<<NCTA, 384, REC_SMEM_L, cudaStreamPerThread>>>(tm_x32, tm_wq, tm_wk, tm_wv, tm_wo, mem0);
    cudaLaunchConfig_t cfg = {};
    cfg.gridDim = dim3(n_aux); cfg.blockDim = dim3(384); cfg.dynamicSmemBytes = GEMM_SMEM; cfg.stream = cudaStreamPerThread;
    cudaLaunchAttribute at[1];
    at[0].id = cudaLaunchAttributeProgrammaticStreamSerialization; at[0].val.programmaticStreamSerializationAllowed = 1;
    cfg.attrs = at; cfg.numAttrs = 1;
    const CUtensorMap ts_qkv = make_map(fn, p_qkvB, 3 * DM, S_LEN, 64, 64), ts_b = make_map(fn, p_oB, DM, S_LEN, 64, 64);
    const CUtensorMap ts_out = make_map(fn, out, DM, S_LEN, 64, 64), ts_acc = make_map(fn, p_acc, DM, 96 * 128, 64, 128);
    cudaLaunchKernelEx(&cfg, aux_kernel, tm_x128, tm_wqkv, tm_oB, tm_woB, tm_oA, tm_wo, ts_qkv, ts_b, ts_out, ts_acc, make_map(fn, p_oA, HD, S_LEN, 64, 64),
                       make_map(fn, Wq, HD, DM, 64, 64), make_map(fn, x, DM, S_LEN, 64, 64), make_map(fn, p_qkvB, 3 * DM, S_LEN, 168, 80, false, false),
                       make_map(fn, p_oB, DM, S_LEN, 160, 32, false, false), make_map(fn, p_Qp, HD, 256, 64, 64), make_map(fn, p_acc, DM, 96 * 128, 64, 64), x, gate_w);
}
```

```cpp
#include <cuda_runtime.h>
#include <cuda_bf16.h>
#include <cuda.h>
#include <stdint.h>
#include <stddef.h>

typedef __nv_bfloat16 bf16;

constexpr int S_LEN = 2048, DM = 640, NH = 32, DH = 192, HD = NH * DH;
constexpr int NSEG = 64;
constexpr int NCTA = 96, NRED = 80;
constexpr int SPIN_MAX = 1 << 22;

__device__ bf16 g_oA[S_LEN * HD];
__device__ bf16 g_Qp[256 * HD];
__device__ __align__(128) char g_kv[(size_t)NSEG * NCTA * 10240];
__device__ bf16 g_qkvB[S_LEN * 3 * DM];
__device__ bf16 g_oB[S_LEN * DM];
__device__ float g_gate[S_LEN];
__device__ char g_rs_raw[4 << 20];
__device__ __align__(32) unsigned g_side[NCTA * 8];
__device__ unsigned g_err;
struct AuxCtl {
    unsigned seg[32];
    unsigned ata[32];
    unsigned at[16], b1[16];
    unsigned qp[32];
    unsigned fin[32];
    unsigned gate, pad0[31];
    unsigned long long next;
    unsigned pad[30];
};
__device__ __align__(128) AuxCtl g_ctl;
__device__ __align__(128) bf16 g_part[128 * 128 * DM];

__device__ __forceinline__ uint32_t smem_u32(const void* p) { return (uint32_t)__cvta_generic_to_shared(p); }
__device__ __forceinline__ uint32_t mapa(uint32_t addr, uint32_t rank) {
    uint32_t r; asm volatile("mapa.shared::cluster.u32 %0, %1, %2;" : "=r"(r) : "r"(addr), "r"(rank)); return r;
}
__device__ __forceinline__ void mbar_init(uint32_t bar, uint32_t cnt) {
    asm volatile("mbarrier.init.shared::cta.b64 [%0], %1;" :: "r"(bar), "r"(cnt) : "memory");
}
__device__ __forceinline__ void mbar_expect(uint32_t bar, uint32_t bytes) {
    asm volatile("mbarrier.arrive.expect_tx.shared::cta.b64 _, [%0], %1;" :: "r"(bar), "r"(bytes) : "memory");
}
__device__ __forceinline__ void mbar_arrive(uint32_t bar) {
    asm volatile("mbarrier.arrive.shared::cta.b64 _, [%0];" :: "r"(bar) : "memory");
}
__device__ __forceinline__ bool mbar_try_cluster(uint32_t bar, uint32_t parity) {
    uint32_t ok;
    asm volatile("{\n.reg .pred p;\nmbarrier.try_wait.parity.acquire.cluster.shared::cta.b64 p, [%1], %2;\nselp.u32 %0, 1, 0, p;\n}"
                 : "=r"(ok) : "r"(bar), "r"(parity) : "memory");
    return ok;
}
__device__ __forceinline__ void mbar_wait(uint32_t bar, uint32_t parity) {
    asm volatile("{\n.reg .pred p;\n.reg .u32 n;\nmov.u32 n, 0;\n"
                 "MW_L_%=:\nmbarrier.try_wait.parity.shared::cta.b64 p, [%0], %1;\n@p bra.uni MW_D_%=;\n"
                 "add.u32 n, n, 1;\nsetp.lt.u32 p, n, %2;\n@p bra.uni MW_L_%=;\n"
                 "st.global.u32 [%3], 1;\nMW_D_%=:\n}"
                 :: "r"(bar), "r"(parity), "n"(SPIN_MAX), "l"(&g_err) : "memory");
}
__device__ __forceinline__ bool elect_one() {
    uint32_t pred;
    asm volatile("{\n.reg .pred P;\nelect.sync _|P, 0xffffffff;\nselp.b32 %0, 1, 0, P;\n}" : "=r"(pred));
    return pred != 0;
}
__device__ __forceinline__ void tma2d(uint32_t dst, const CUtensorMap* tm, int c0, int c1, uint32_t bar) {
    asm volatile("cp.async.bulk.tensor.2d.shared::cluster.global.mbarrier::complete_tx::bytes [%0], [%1, {%3, %4}], [%2];"
                 :: "r"(dst), "l"(tm), "r"(bar), "r"(c0), "r"(c1) : "memory");
}
__device__ __forceinline__ void tma2d_prefetch(const CUtensorMap* tm, int c0, int c1) {
    asm volatile("cp.async.bulk.prefetch.tensor.2d.L2.global [%0, {%1, %2}];" :: "l"(tm), "r"(c0), "r"(c1) : "memory");
}
__device__ __forceinline__ void bar_sync(int id, int n) { asm volatile("barrier.sync %0, %1;" :: "r"(id), "r"(n) : "memory"); }
__device__ __forceinline__ void bar_sync_dep(int id, int n, uint32_t dep) {
    asm volatile("{ .reg .u32 t; min.u32 t, %2, %1; max.u32 t, t, %1; barrier.sync %0, t; }" :: "r"(id), "r"(n), "r"(dep) : "memory");
}
__device__ __forceinline__ void bar_arrive_dep(int id, int n, uint32_t dep) {
    asm volatile("{ .reg .u32 t; min.u32 t, %2, %1; max.u32 t, t, %1; barrier.arrive %0, t; }" :: "r"(id), "r"(n), "r"(dep) : "memory");
}
__device__ __forceinline__ void bar_arrive(int id, int n) { asm volatile("barrier.arrive %0, %1;" :: "r"(id), "r"(n) : "memory"); }
__device__ __forceinline__ void fence_async_smem() { asm volatile("fence.proxy.async.shared::cta;" ::: "memory"); }
__device__ __forceinline__ void cluster_sync() {
    asm volatile("barrier.cluster.arrive.release;\nbarrier.cluster.wait.acquire;" ::: "memory");
}
__device__ __forceinline__ void ldsm4(uint32_t& r0, uint32_t& r1, uint32_t& r2, uint32_t& r3, uint32_t a) {
    asm volatile("ldmatrix.sync.aligned.m8n8.x4.shared.b16 {%0,%1,%2,%3}, [%4];" : "=r"(r0), "=r"(r1), "=r"(r2), "=r"(r3) : "r"(a) : "memory");
}
__device__ __forceinline__ void ldsm4t(uint32_t& r0, uint32_t& r1, uint32_t& r2, uint32_t& r3, uint32_t a) {
    asm volatile("ldmatrix.sync.aligned.m8n8.x4.trans.shared.b16 {%0,%1,%2,%3}, [%4];" : "=r"(r0), "=r"(r1), "=r"(r2), "=r"(r3) : "r"(a) : "memory");
}
__device__ __forceinline__ void ldsm2t(uint32_t& r0, uint32_t& r1, uint32_t a) {
    asm volatile("ldmatrix.sync.aligned.m8n8.x2.trans.shared.b16 {%0,%1}, [%2];" : "=r"(r0), "=r"(r1) : "r"(a) : "memory");
}
__device__ __forceinline__ void ldsm2(uint32_t& r0, uint32_t& r1, uint32_t a) {
    asm volatile("ldmatrix.sync.aligned.m8n8.x2.shared.b16 {%0,%1}, [%2];" : "=r"(r0), "=r"(r1) : "r"(a) : "memory");
}
__device__ __forceinline__ void bulk_g2s(uint32_t dst, const void* src, uint32_t bytes, uint32_t bar) {
    asm volatile("cp.async.bulk.shared::cluster.global.mbarrier::complete_tx::bytes [%0], [%1], %2, [%3];" :: "r"(dst), "l"(src), "r"(bytes), "r"(bar) : "memory");
}
__device__ __forceinline__ uint64_t pol_stream() { uint64_t p; asm volatile("createpolicy.fractional.L2::evict_first.b64 %0, 1.0;" : "=l"(p)); return p; }
__device__ __forceinline__ void bulk_g2s_s(uint32_t dst, const void* src, uint32_t bytes, uint32_t bar, uint64_t pol) {
    asm volatile("cp.async.bulk.shared::cluster.global.mbarrier::complete_tx::bytes.L2::cache_hint [%0], [%1], %2, [%3], %4;" :: "r"(dst), "l"(src), "r"(bytes), "r"(bar), "l"(pol) : "memory");
}
__device__ __forceinline__ void tma2d_s(uint32_t dst, const CUtensorMap* tm, int c0, int c1, uint32_t bar, uint64_t pol) {
    asm volatile("cp.async.bulk.tensor.2d.shared::cluster.global.mbarrier::complete_tx::bytes.L2::cache_hint [%0], [%1, {%3, %4}], [%2], %5;"
                 :: "r"(dst), "l"(tm), "r"(bar), "r"(c0), "r"(c1), "l"(pol) : "memory");
}
__device__ __forceinline__ void stsm4(uint32_t a, uint32_t r0, uint32_t r1, uint32_t r2, uint32_t r3) {
    asm volatile("stmatrix.sync.aligned.m8n8.x4.shared.b16 [%0], {%1,%2,%3,%4};" :: "r"(a), "r"(r0), "r"(r1), "r"(r2), "r"(r3) : "memory");
}
__device__ __forceinline__ void mma16816(float* c, uint32_t a0, uint32_t a1, uint32_t a2, uint32_t a3, uint32_t b0, uint32_t b1) {
    asm volatile("mma.sync.aligned.m16n8k16.row.col.f32.bf16.bf16.f32 {%0,%1,%2,%3}, {%4,%5,%6,%7}, {%8,%9}, {%0,%1,%2,%3};"
                 : "+f"(c[0]), "+f"(c[1]), "+f"(c[2]), "+f"(c[3]) : "r"(a0), "r"(a1), "r"(a2), "r"(a3), "r"(b0), "r"(b1));
}
__device__ __forceinline__ void mma1688(float* c, uint32_t a0, uint32_t a1, uint32_t b0) {
    asm volatile("mma.sync.aligned.m16n8k8.row.col.f32.bf16.bf16.f32 {%0,%1,%2,%3}, {%4,%5}, {%6}, {%0,%1,%2,%3};"
                 : "+f"(c[0]), "+f"(c[1]), "+f"(c[2]), "+f"(c[3]) : "r"(a0), "r"(a1), "r"(b0));
}
__device__ __forceinline__ uint32_t pack_bf16(float lo, float hi) {
    uint32_t r; asm("cvt.rn.bf16x2.f32 %0, %1, %2;" : "=r"(r) : "f"(hi), "f"(lo)); return r;
}
__device__ __forceinline__ uint32_t nz(uint32_t w) { return w == 0u ? 0x80000000u : w; }
__device__ __forceinline__ void sts32(uint32_t a, uint32_t v) { asm volatile("st.shared.u32 [%0], %1;" :: "r"(a), "r"(v) : "memory"); }
__device__ __forceinline__ void sts64f(uint32_t a, float x, float y) { asm volatile("st.shared.v2.f32 [%0], {%1,%2};" :: "r"(a), "f"(x), "f"(y) : "memory"); }
__device__ __forceinline__ void sts128(uint32_t a, uint4 v) {
    asm volatile("st.shared.v4.u32 [%0], {%1,%2,%3,%4};" :: "r"(a), "r"(v.x), "r"(v.y), "r"(v.z), "r"(v.w) : "memory");
}
__device__ __forceinline__ float4 lds128f(uint32_t a) {
    float4 v; asm volatile("ld.shared.v4.f32 {%0,%1,%2,%3}, [%4];" : "=f"(v.x), "=f"(v.y), "=f"(v.z), "=f"(v.w) : "r"(a) : "memory"); return v;
}
__device__ __forceinline__ float2 lds64f(uint32_t a) {
    float2 v; asm volatile("ld.shared.v2.f32 {%0,%1}, [%2];" : "=f"(v.x), "=f"(v.y) : "r"(a) : "memory"); return v;
}
__device__ __forceinline__ void st_async4(uint32_t a, uint32_t x, uint32_t y, uint32_t z, uint32_t w, uint32_t bar) {
    asm volatile("st.async.weak.shared::cluster.mbarrier::complete_tx::bytes.v4.b32 [%0], {%1,%2,%3,%4}, [%5];"
                 :: "r"(a), "r"(x), "r"(y), "r"(z), "r"(w), "r"(bar) : "memory");
}
__device__ __forceinline__ void st_async2(uint32_t a, uint32_t x, uint32_t y, uint32_t bar) {
    asm volatile("st.async.weak.shared::cluster.mbarrier::complete_tx::bytes.v2.b32 [%0], {%1,%2}, [%3];" :: "r"(a), "r"(x), "r"(y), "r"(bar) : "memory");
}
__device__ __forceinline__ void st_async1(uint32_t a, uint32_t x, uint32_t bar) {
    asm volatile("st.async.weak.shared::cluster.mbarrier::complete_tx::bytes.b32 [%0], %1, [%2];" :: "r"(a), "r"(x), "r"(bar) : "memory");
}
__device__ __forceinline__ void sts64(uint32_t a, uint32_t x, uint32_t y) { asm volatile("st.shared.v2.u32 [%0], {%1,%2};" :: "r"(a), "r"(x), "r"(y) : "memory"); }
__device__ __forceinline__ uint4 ld_relaxed4(const void* p) {
    uint4 v; asm volatile("ld.relaxed.gpu.global.v4.u32 {%0,%1,%2,%3}, [%4];" : "=r"(v.x), "=r"(v.y), "=r"(v.z), "=r"(v.w) : "l"(p) : "memory"); return v;
}
__device__ __forceinline__ uint32_t ld_relaxed1(const void* p) {
    uint32_t v; asm volatile("ld.relaxed.gpu.global.u32 %0, [%1];" : "=r"(v) : "l"(p) : "memory"); return v;
}
__device__ __forceinline__ void st_relaxed4(void* p, uint4 v) {
    asm volatile("st.relaxed.gpu.global.v4.u32 [%0], {%1,%2,%3,%4};" :: "l"(p), "r"(v.x), "r"(v.y), "r"(v.z), "r"(v.w) : "memory");
}
__device__ __forceinline__ void st_relaxed1(void* p, uint32_t v) {
    asm volatile("st.relaxed.gpu.global.u32 [%0], %1;" :: "l"(p), "r"(v) : "memory");
}
template <int LUT> __device__ __forceinline__ uint32_t lop3(uint32_t a, uint32_t b, uint32_t c) {
    uint32_t r; asm("lop3.b32 %0, %1, %2, %3, %4;" : "=r"(r) : "r"(a), "r"(b), "r"(c), "n"(LUT)); return r;
}
__device__ __forceinline__ void st_relaxed1_split(uint32_t lo, uint32_t hi, uint32_t v) {
    asm volatile("{ .reg .b64 a; mov.b64 a, {%0, %1}; st.relaxed.gpu.global.u32 [a], %2; }" :: "r"(lo), "r"(hi), "r"(v) : "memory");
}
__device__ __forceinline__ bool allnz(const uint4& v) { return min(min(v.x, v.y), min(v.z, v.w)) != 0u; }
__device__ __forceinline__ float ex2(float x) { float r; asm("ex2.approx.ftz.f32 %0, %1;" : "=f"(r) : "f"(x)); return r; }
#define WG_ROT 0
__device__ __forceinline__ int vtid() { return ((int)threadIdx.x + WG_ROT * 128) % 384; }
__device__ __forceinline__ int tid_pinned() { return __shfl_sync(0xffffffffu, vtid(), threadIdx.x & 31); }
__device__ __forceinline__ int opaque(int x) { int t; asm volatile("mov.u32 %0, %1;" : "=r"(t) : "r"(x)); return t; }
__device__ __forceinline__ const uint4* opaque_ptr(const uint4* p) { const uint4* r; asm volatile("mov.b64 %0, %1;" : "=l"(r) : "l"(p)); return r; }
__device__ __forceinline__ unsigned clk_dep(uint32_t dep) {
    unsigned t; asm volatile("{ .reg .pred p; .reg .u32 x; min.u32 x, %1, 7; setp.le.u32 p, x, 7; mov.u32 %0, 0; @p mov.u32 %0, %%clock; }" : "=r"(t) : "r"(dep) : "memory"); return t;
}
__device__ __forceinline__ unsigned gt32() { unsigned t; asm volatile("mov.u32 %0, %%globaltimer_lo;" : "=r"(t) :: "memory"); return t; }
__device__ __forceinline__ unsigned clk32() { unsigned t; asm volatile("mov.u32 %0, %%clock;" : "=r"(t) :: "memory"); return t; }

__device__ __forceinline__ void wg_fence() { asm volatile("wgmma.fence.sync.aligned;" ::: "memory"); }
__device__ __forceinline__ void wg_commit() { asm volatile("wgmma.commit_group.sync.aligned;" ::: "memory"); }
template <int N> __device__ __forceinline__ void wg_wait() { asm volatile("wgmma.wait_group.sync.aligned %0;" :: "n"(N) : "memory"); }
__host__ __device__ constexpr uint64_t make_desc(uint32_t addr, uint32_t lbo, uint32_t sbo, uint32_t swz) {
    return (uint64_t)((addr & 0x3FFFF) >> 4) | ((uint64_t)(lbo >> 4) << 16) | ((uint64_t)(sbo >> 4) << 32) | ((uint64_t)swz << 62);
}
#define ACC16(d) "+f"(d[0]), "+f"(d[1]), "+f"(d[2]), "+f"(d[3]), "+f"(d[4]), "+f"(d[5]), "+f"(d[6]), "+f"(d[7]), \
                 "+f"(d[8]), "+f"(d[9]), "+f"(d[10]), "+f"(d[11]), "+f"(d[12]), "+f"(d[13]), "+f"(d[14]), "+f"(d[15])
__device__ __forceinline__ void wgmma_rs_n32(float* d, const uint32_t* a, uint64_t db, int acc) {
    asm volatile("{\n.reg .pred p;\nsetp.ne.b32 p, %21, 0;\n"
                 "wgmma.mma_async.sync.aligned.m64n32k16.f32.bf16.bf16 {%0,%1,%2,%3,%4,%5,%6,%7,%8,%9,%10,%11,%12,%13,%14,%15}, {%16,%17,%18,%19}, %20, p, 1, 1, 0;\n}"
                 : ACC16(d) : "r"(a[0]), "r"(a[1]), "r"(a[2]), "r"(a[3]), "l"(db), "r"(acc));
}
#define OUT16(d) "=f"(d[0]), "=f"(d[1]), "=f"(d[2]), "=f"(d[3]), "=f"(d[4]), "=f"(d[5]), "=f"(d[6]), "=f"(d[7]), \
                 "=f"(d[8]), "=f"(d[9]), "=f"(d[10]), "=f"(d[11]), "=f"(d[12]), "=f"(d[13]), "=f"(d[14]), "=f"(d[15])
__device__ __forceinline__ void wgmma_rs_n32_first(float* d, const uint32_t* a, uint64_t db) {
    asm volatile("wgmma.mma_async.sync.aligned.m64n32k16.f32.bf16.bf16 {%0,%1,%2,%3,%4,%5,%6,%7,%8,%9,%10,%11,%12,%13,%14,%15}, {%16,%17,%18,%19}, %20, 0, 1, 1, 0;"
                 : OUT16(d) : "r"(a[0]), "r"(a[1]), "r"(a[2]), "r"(a[3]), "l"(db));
}
__device__ __forceinline__ void wgmma_ss_n32_ta(float* d, uint64_t da, uint64_t db, int acc) {
    asm volatile("{\n.reg .pred p;\nsetp.ne.b32 p, %18, 0;\n"
                 "wgmma.mma_async.sync.aligned.m64n32k16.f32.bf16.bf16 {%0,%1,%2,%3,%4,%5,%6,%7,%8,%9,%10,%11,%12,%13,%14,%15}, %16, %17, p, 1, 1, 1, 0;\n}"
                 : ACC16(d) : "l"(da), "l"(db), "r"(acc));
}
__device__ __forceinline__ void wgmma_ss_n32_ta_first(float* d, uint64_t da, uint64_t db) {
    asm volatile("wgmma.mma_async.sync.aligned.m64n32k16.f32.bf16.bf16 {%0,%1,%2,%3,%4,%5,%6,%7,%8,%9,%10,%11,%12,%13,%14,%15}, %16, %17, 0, 1, 1, 1, 0;"
                 : OUT16(d) : "l"(da), "l"(db));
}
__device__ __forceinline__ void wgmma_ss_n8_tatb(float* d, uint64_t da, uint64_t db, int acc) {
    asm volatile("{\n.reg .pred p;\nsetp.ne.b32 p, %6, 0;\n"
                 "wgmma.mma_async.sync.aligned.m64n8k16.f32.bf16.bf16 {%0,%1,%2,%3}, %4, %5, p, 1, 1, 1, 1;\n}"
                 : "+f"(d[0]), "+f"(d[1]), "+f"(d[2]), "+f"(d[3]) : "l"(da), "l"(db), "r"(acc));
}

__device__ __forceinline__ void wgmma_ss_n40_tatb(float* d, uint64_t da, uint64_t db, int acc) {
    asm volatile("{\n.reg .pred p;\nsetp.ne.b32 p, %22, 0;\n"
                 "wgmma.mma_async.sync.aligned.m64n40k16.f32.bf16.bf16 {%0,%1,%2,%3,%4,%5,%6,%7,%8,%9,%10,%11,%12,%13,%14,%15,%16,%17,%18,%19}, %20, %21, p, 1, 1, 1, 1;\n}"
                 : ACC16(d), "+f"(d[16]), "+f"(d[17]), "+f"(d[18]), "+f"(d[19]) : "l"(da), "l"(db), "r"(acc));
}
__device__ __forceinline__ void wgmma_rs_n32x(float* d, uint32_t a0, uint32_t a1, uint32_t a2, uint32_t a3, uint64_t db, int acc) {
    const uint32_t a[4] = {a0, a1, a2, a3};
    wgmma_rs_n32(d, a, db, acc);
}
__device__ __forceinline__ float rcp(float x) { float r; asm("rcp.approx.ftz.f32 %0, %1;" : "=f"(r) : "f"(x)); return r; }
__device__ __forceinline__ uint4 lds128(uint32_t a) {
    uint4 v; asm volatile("ld.shared.v4.u32 {%0,%1,%2,%3}, [%4];" : "=r"(v.x), "=r"(v.y), "=r"(v.z), "=r"(v.w) : "r"(a) : "memory"); return v;
}
__device__ __forceinline__ uint2 lds64(uint32_t a) { uint2 v; asm volatile("ld.shared.v2.u32 {%0,%1}, [%2];" : "=r"(v.x), "=r"(v.y) : "r"(a) : "memory"); return v; }
__device__ __forceinline__ uint32_t lds32(uint32_t a) { uint32_t v; asm volatile("ld.shared.u32 %0, [%1];" : "=r"(v) : "r"(a) : "memory"); return v; }
__device__ __forceinline__ uint32_t hadd2(uint32_t a, uint32_t b) { uint32_t r; asm("add.rn.bf16x2 %0, %1, %2;" : "=r"(r) : "r"(a), "r"(b)); return r; }
__device__ __forceinline__ uint32_t hmax2(uint32_t a, uint32_t b) { uint32_t r; asm("max.bf16x2 %0, %1, %2;" : "=r"(r) : "r"(a), "r"(b)); return r; }
__device__ __forceinline__ float bf_lo(uint32_t w) { return __uint_as_float(w << 16); }
__device__ __forceinline__ float bf_hi(uint32_t w) { return __uint_as_float(w & 0xffff0000u); }

constexpr uint32_t SB0 = 1024;
constexpr uint32_t SM_WQ = 0;
constexpr uint32_t SM_WO = 81920;
constexpr uint32_t SM_XR = 163840;
constexpr uint32_t SM_MEM = SM_XR + 10 * 4096;
constexpr uint32_t SM_KB = SM_MEM + 10240;
constexpr uint32_t SM_VB = SM_KB + 5120;
constexpr uint32_t SM_SC = SM_VB + 5120;
constexpr uint32_t SM_XIN = SM_SC + 5120;
constexpr uint32_t SM_BAR = SM_SC + 512;
constexpr uint32_t SM_IB = SM_SC + 640 + 512;
constexpr uint32_t SM_PB = SM_SC + 2 * 640 + 512;
constexpr uint32_t REC_SMEM = SM_XIN + 2048;
constexpr uint32_t REC_SMEM_L = REC_SMEM;
static_assert(REC_SMEM_L <= 232448, "smem");
constexpr uint32_t MB_W0 = 0, MB_W1 = 8, MB_X = 24, MB_W2 = 32, MB_G = 40;
constexpr int NB_ALL = 1, NB_TS = 2, NB_QK = 3, NB_O = 5, NB_XR = 7, NB_TA = 8, NB_WG2 = 9, NB_PUB = 10, NB_X0 = 11;

constexpr float SCALE_A = 0.07216878364870322f * 1.4426950408889634f;
#define R_WG0 208
#define R_WG2 88
#define Q_PF 6
#define O_PF 2
#define EVX 1
#define POLL_P 130
#define QA_AT 0
#define QA_N 3
#define QB_AT 19
#define SW_AT 2
#define COLD_D 400
#define O_PFN 6
#define FIN_EARLY 1
#define PAUSE 1
#define SECMAJ 1
#define RS_CH 3
#define AG_D 330
#define AG_E 0
#define RS_AT 1200
#define AG_AT 2050
#define X_AT 0

__device__ __forceinline__ char* rs_base() { return (char*)(((uintptr_t)g_rs_raw + (2 << 20) - 1) & ~(uintptr_t)((2 << 20) - 1)); }
__device__ __forceinline__ uint32_t hashbit(uint32_t a) { return ((a >> 12) ^ (a >> 13) ^ (a >> 16) ^ (a >> 17) ^ (a >> 19)) & 1u; }
__device__ __forceinline__ uint32_t rs_off(int r, uint32_t side) {
    const uint32_t a = r * 8192;
    return a + ((side ^ hashbit(a)) << 12);
}
constexpr uint32_t AG_BASE = NRED * 8192;
__device__ __forceinline__ uint32_t ag_off(int b, uint32_t side) {
    const uint32_t a = AG_BASE + b * 8192;
    return a + ((side ^ hashbit(a)) << 12);
}
__device__ __forceinline__ uint32_t get_epoch() { return ld_relaxed1(&g_ctl.gate) >> 9; }
__device__ __forceinline__ uint32_t get_side(int cta, uint32_t epoch) {
    uint32_t v; int n = 0;
#pragma unroll 1
    do { v = ld_relaxed1(&g_side[cta * 8]); } while ((v >> 1) != epoch + 1 && ++n < SPIN_MAX);
    return v & 1u;
}
__device__ __forceinline__ void spin_until(unsigned t0, unsigned d) {
    asm volatile("{\n.reg .pred p;\n.reg .u32 t, h;\n.reg .u64 c;\nSU_L_%=:\nmov.u64 c, %%clock64;\nmov.b64 {t, h}, c;\nsub.u32 t, t, %0;\nand.b32 h, h, 0x80000000;\nor.b32 t, t, h;\nsetp.lt.u32 p, t, %1;\n@p bra.uni SU_L_%=;\n}"
                 :: "r"(t0), "r"(d) : "memory");
}
__device__ __forceinline__ void cpa16(uint32_t dst, const void* src) {
    asm volatile("cp.async.cg.shared.global [%0], [%1], 16;" :: "r"(dst), "l"(src) : "memory");
}
__device__ __forceinline__ void cpa_wait() { asm volatile("cp.async.wait_all;" ::: "memory"); }
__device__ __forceinline__ void cpa_commit() { asm volatile("cp.async.commit_group;" ::: "memory"); }
__device__ __forceinline__ void cpa_wait2() { asm volatile("cp.async.wait_group 2;" ::: "memory"); }

__device__ __forceinline__ void issue_x(uint32_t sb, const CUtensorMap* tm_x, int seg, int g) {
    mbar_expect(sb + SM_BAR + MB_G + 8 * g, 20480);
    asm volatile("cp.async.bulk.tensor.3d.shared::cluster.global.mbarrier::complete_tx::bytes [%0], [%1, {0, %3, %4}], [%2];"
                 :: "r"(sb + SM_XR + g * 20480), "l"(tm_x), "r"(sb + SM_BAR + MB_G + 8 * g), "r"(seg * 32), "r"(5 * g) : "memory");
}
__device__ __forceinline__ uint64_t mk64(uint32_t lo, uint32_t hi) { uint64_t r; asm("mov.b64 %0, {%1, %2};" : "=l"(r) : "r"(lo), "r"(hi)); return r; }
template <int OFF> __device__ __forceinline__ void st_relaxed1_a(uint64_t a, uint32_t v) {
    asm volatile("st.relaxed.gpu.global.u32 [%0 + %2], %1;" :: "l"(a), "r"(v), "n"(OFF) : "memory");
}
#define PIN1(a) asm volatile("" :: "r"(a));
#define PIN2(a, b) asm volatile("" :: "r"(a), "r"(b));
#define PINL(a) asm volatile("" :: "l"(a));
#define PINF(a) asm volatile("" :: "f"((a)[0]), "f"((a)[1]), "f"((a)[2]), "f"((a)[3]));
template <int OFF> __device__ __forceinline__ void st_relaxed1_off(uint32_t lo, uint32_t hi, uint32_t v) {
    asm volatile("{ .reg .b64 a; mov.b64 a, {%0, %1}; st.relaxed.gpu.global.u32 [a + %3], %2; }" :: "r"(lo), "r"(hi), "r"(v), "n"(OFF) : "memory");
}
template <int OFF> __device__ __forceinline__ uint32_t ld_relaxed1_off(const void* p) {
    uint32_t v; asm volatile("ld.relaxed.gpu.global.u32 %0, [%1 + %2];" : "=r"(v) : "l"(p), "n"(OFF) : "memory"); return v;
}

constexpr uint64_t DESC_X = make_desc(SB0 + SM_XR, 16, 1024, 1);
#define XOFF(k) ((((k) / 4) * 4096 + ((k) % 4) * 32) >> 4)

#define SCHED_FENCE asm volatile("{\n.reg .pred p;\nsetp.eq.u32 p, %0, 0;\n@p exit;\n}" :: "r"(sb) : "memory");
#define LD_T(buf, a) { ldsm4t((buf)[0], (buf)[1], (buf)[2], (buf)[3], a); }
#define LD_Q(i) LD_T(Q[i], ta + SM_WQ + (20 * G + (i)) * 2048)
template <int G, bool FIRST>
__device__ __forceinline__ void token_gemm(uint32_t sb, const uint32_t (&W)[160], uint32_t (&Q)[Q_PF][4], uint32_t ta, int seg, int tx, int wu) {
    const int lane = tx & 31;
    float a[16];
    wg_fence();
#pragma unroll
    for (int k = 0; k < 20; k++) {
        if (k == 0) wgmma_rs_n32_first(a, W, DESC_X + XOFF(20 * G)); else wgmma_rs_n32(a, &W[k * 4], DESC_X + XOFF(20 * G + k), 1);
        if (!FIRST && k == QA_AT) {
            __syncwarp();
#pragma unroll
            for (int i = 0; i < QA_N; i++) LD_Q(i)
            __syncwarp();
        }
    }
    wg_commit();
    const uint32_t off = sb + wu * 1280 + (((lane >> 3) & 1) * 5 + (lane >> 4)) * 128 + (lane & 7) * 16;
    const uint32_t b1 = off + (G == 0 ? SM_KB : SM_VB), b2 = off + (G == 0 ? SM_VB : SM_KB);
    wg_wait<0>();
    uint32_t u[8];
#pragma unroll
    for (int i = 0; i < 8; i++) u[i] = pack_bf16(a[2 * i], a[2 * i + 1]);
    if (!FIRST && PAUSE) bar_sync(NB_PUB, 384);
    stsm4(b1, u[0], u[1], u[2], u[3]); stsm4(b1 + 256, u[4], u[5], u[6], u[7]);
    bar_sync(NB_TA, 256);
    wg_fence();
#pragma unroll
    for (int k = 0; k < 20; k++) {
        if (k == 0) wgmma_rs_n32_first(a, &W[80], DESC_X + XOFF(20 * G)); else wgmma_rs_n32(a, &W[80 + k * 4], DESC_X + XOFF(20 * G + k), 1);
        if (k == QB_AT) {
            __syncwarp();
            ldsm4(u[0], u[1], u[2], u[3], b2); ldsm4(u[4], u[5], u[6], u[7], b2 + 256);
            if (!FIRST) {
#pragma unroll
                for (int i = QA_N; i < 4; i++) LD_Q(i)
            }
            __syncwarp();
        }
    }
    wg_commit();
    wg_wait<0>();
#pragma unroll
    for (int i = 0; i < 8; i++) u[i] = hadd2(pack_bf16(a[2 * i], a[2 * i + 1]), u[i]);
    stsm4(b2, u[0], u[1], u[2], u[3]); stsm4(b2 + 256, u[4], u[5], u[6], u[7]);
    if (FIRST) mbar_wait(sb + SM_BAR + MB_W1, 0);
#pragma unroll
    for (int i = FIRST ? 0 : 4; i < Q_PF; i++) LD_Q(i)
}
#undef LD_Q

#define LD_O(buf, a) { _Pragma("unroll") for (int ks = 0; ks < 4; ks++) ldsm4t((buf)[4 * ks], (buf)[4 * ks + 1], (buf)[4 * ks + 2], (buf)[4 * ks + 3], (a) + ks * 2048); }
#define MMA_K(c, P, ks) mma16816(c, P[4 * (ks)], P[4 * (ks) + 1], P[4 * (ks) + 2], P[4 * (ks) + 3], B[2 * (ks)], B[2 * (ks) + 1]);
#define MMA_O(c, P) { MMA_K(c, P, 0) MMA_K(c, P, 1) MMA_K(c, P, 2) MMA_K(c, P, 3) }
__host__ __device__ constexpr int qload(int j) {
    int n = 0;
    for (int k = 0; k < 20; k++) {
        if (!(k & 1)) { if (n == j) return k >> 1; n++; }
        if (k >= Q_PF) { if (n == j) return 10 + k; n++; }
    }
    return -1;
}

template <int G>
__device__ __forceinline__ void rec_weights(uint32_t sb, uint32_t rank, const CUtensorMap* tm_x, const CUtensorMap* tm_wq,
                                            const CUtensorMap* tm_wo, int head) {
    const int tx0 = tid_pinned();
    const int wu = __shfl_sync(0xffffffffu, (int)(threadIdx.x >> 5) & 3, 0);
    uint32_t W[160];
    mbar_wait(sb + SM_BAR + MB_W0, 0);
    {
        const int lane = tx0 & 31;
        const uint32_t d = ((lane >> 4) & 1) * 8 + (lane & 7), ch = 2 * wu + ((lane >> 3) & 1);
        const uint32_t a = sb + d * 128 + ((ch ^ (d & 7)) << 4) + G * 20 * 2048;
#pragma unroll
        for (int k = 0; k < 20; k++) LD_T(&W[4 * k], a + (G == 0 ? SM_WO : SM_WQ) + k * 2048)
#pragma unroll
        for (int k = 0; k < 20; k++) LD_T(&W[80 + 4 * k], a + (G == 0 ? SM_WQ : SM_WO) + k * 2048)
    }
    bar_sync(NB_TA, 256);
    if (G == 0 && wu == 0) {
        if (elect_one()) {
            mbar_expect(sb + SM_BAR + MB_W1, 81920);
            mbar_expect(sb + SM_BAR + MB_W2, 81920);
#pragma unroll
            for (int i = 0; i < 5; i++) tma2d(sb + SM_WQ + i * 16384, tm_wq, head * DH + rank * 64, i * 128, sb + SM_BAR + MB_W1);
#pragma unroll
            for (int i = 0; i < 10; i++) tma2d(sb + SM_WO + i * 8192, tm_wo, i * 64, head * DH + rank * 64, sb + SM_BAR + MB_W2);
        }
        __syncwarp();
    }
    asm volatile("barrier.cluster.wait.acquire;" ::: "memory");
    mbar_wait(sb + SM_BAR + MB_G + 8 * G, 0);
    const uint32_t ta = sb + (((tx0 >> 4) & 1) * 8 + (tx0 & 7)) * 128 + (((2 * wu + ((tx0 >> 3) & 1)) ^ (tx0 & 7)) << 4);
    const uint32_t mb = __shfl_sync(0xffffffffu, sb + (tx0 & 31) * 16 + SM_MEM + G * 5120, tx0 & 31);
    uint32_t QP[Q_PF][4];
    token_gemm<G, true>(sb, W, QP, ta, 0, opaque(tx0), wu);
    char* kvp = g_kv + (size_t)blockIdx.x * 10240 + (1 - G) * 5120 + wu * 1280;
    const uint32_t dest = (rank + 1 + G) % 3;
    for (int s = 0; s < NSEG; s++) {
        {
            uint32_t Q[20][4], b[10][4];
#pragma unroll
            for (int i = 0; i < Q_PF; i++) { Q[i][0] = QP[i][0]; Q[i][1] = QP[i][1]; Q[i][2] = QP[i][2]; Q[i][3] = QP[i][3]; }
            bar_sync(NB_ALL, 384);
            float cq[4] = {0.f, 0.f, 0.f, 0.f}, ck[4] = {0.f, 0.f, 0.f, 0.f}, cv[4] = {0.f, 0.f, 0.f, 0.f};
#define QLD(j) { constexpr int x_ = qload(j); if (x_ >= 10) LD_T(Q[x_ >= 10 ? x_ - 10 : 0], ta + SM_WQ + (20 * G + x_ - 10) * 2048) else if (x_ >= 0) LD_T(b[x_ >= 0 && x_ < 10 ? x_ : 0], mb + x_ * 512) }
#define QSTEP(k) { \
                mma16816(cq, Q[k][0], Q[k][1], Q[k][2], Q[k][3], b[(k) >> 1][2 * ((k) & 1)], b[(k) >> 1][2 * ((k) & 1) + 1]); \
                if ((k) > 0) QLD(Q_NI - 1 + (k) + ((k) >> 1)) \
                SCHED_FENCE \
                mma16816(ck, W[80 * G + 4 * (k)], W[80 * G + 4 * (k) + 1], W[80 * G + 4 * (k) + 2], W[80 * G + 4 * (k) + 3], b[(k) >> 1][2 * ((k) & 1)], b[(k) >> 1][2 * ((k) & 1) + 1]); \
                mma16816(cv, W[80 - 80 * G + 4 * (k)], W[80 - 80 * G + 4 * (k) + 1], W[80 - 80 * G + 4 * (k) + 2], W[80 - 80 * G + 4 * (k) + 3], b[(k) >> 1][2 * ((k) & 1)], b[(k) >> 1][2 * ((k) & 1) + 1]); \
                if ((k) & 1) QLD(Q_NI + (k) + ((k) >> 1)) \
                SCHED_FENCE }
            constexpr int Q_NI = 8 - Q_PF;
            QLD(0) if (Q_NI > 1) QLD(1) if (Q_NI > 2) QLD(2)
            SCHED_FENCE
            QSTEP(0) QSTEP(1) QSTEP(2) QSTEP(3) QSTEP(4) QSTEP(5) QSTEP(6) QSTEP(7) QSTEP(8) QSTEP(9)
            QSTEP(10) QSTEP(11) QSTEP(12) QSTEP(13) QSTEP(14) QSTEP(15) QSTEP(16) QSTEP(17)
            const uint32_t a = sb + ((opaque((int)mb) >> 4) & 31) * 4 + wu * 1280;
            QSTEP(18) QSTEP(19)
#undef QSTEP
#undef QLD
            constexpr uint32_t ok = G == 0 ? SM_KB + 512 : SM_SC + 256, ov = G == 0 ? SM_VB + 512 : SM_SC + 384;
            sts32(a + SM_SC + G * 128, pack_bf16(cq[0], cq[1])); sts32(a + SM_SC + G * 128 + 640, pack_bf16(cq[2], cq[3]));
            sts32(a + ok, pack_bf16(ck[0], ck[1])); sts32(a + ok + 640, pack_bf16(ck[2], ck[3]));
            sts32(a + ov, pack_bf16(cv[0], cv[1])); sts32(a + ov + 640, pack_bf16(cv[2], cv[3]));
        }
        bar_arrive(NB_XR, 352);
        bar_arrive(NB_X0, 288);
        {
            const int tx = (opaque((int)mb) >> 4);
            const uint32_t oa = ta + SM_WO + 3 * 8192 * dest;
            uint32_t A[16], A2[16], A3[16];
            if (s == 0) mbar_wait(sb + SM_BAR + MB_W2, 0);
            {
                const uint32_t a = sb + (tx & 31) * 4 + wu * 1280;
                constexpr uint32_t of = (G == 0 ? SM_VB : SM_KB) + 512, op = SM_SC + 384 - G * 128;
                PIN1(a)
                SCHED_FENCE
                bar_sync(NB_QK, 384);
                const uint32_t y0 = lds32(a + of), y1 = lds32(a + op), y2 = lds32(a + of + 640), y3 = lds32(a + op + 640);
                SCHED_FENCE
                LD_O(A, oa)
                SCHED_FENCE
                LD_T(&A2[0], oa + 8192) LD_T(&A2[4], oa + 8192 + 2048)
                if (O_PFN > 6) LD_T(&A2[8], oa + 8192 + 2 * 2048)
                if (O_PFN > 7) LD_T(&A2[12], oa + 8192 + 3 * 2048)
                SCHED_FENCE
                sts32(a + of, hadd2(y0, y1)); sts32(a + of + 640, hadd2(y2, y3));
                fence_async_smem();
                __syncwarp();
                asm volatile("{\n.reg .pred p;\nelect.sync _|p, 0xffffffff;\n"
                             "@p cp.async.bulk.global.shared::cta.bulk_group.L2::cache_hint [%0], [%1], 1280, %2;\n"
                             "cp.async.bulk.commit_group;\n}"
                             :: "l"(kvp), "r"(sb + SM_KB + (1 - G) * 5120 + wu * 1280), "l"(pol_stream()) : "memory");
                kvp += NCTA * 10240;
                if (O_PFN < 7) LD_T(&A2[8], oa + 8192 + 2 * 2048)
                if (O_PFN < 8) LD_T(&A2[12], oa + 8192 + 3 * 2048)
            }
            if (s == NSEG - 1) {
                asm volatile("cp.async.bulk.wait_group 0;" ::: "memory");
                bar_sync(NB_TA, 256);
                if (G == 0 && wu == 0 && elect_one()) {
                    asm volatile("red.release.gpu.global.add.u32 [%0], 2;" :: "l"(&g_ctl.seg[31]) : "memory");
                }
                break;
            }
            const uint32_t dd = (dest - rank) << 24;
            const uint32_t ib = sb + dd + SM_IB + wu * 8, id = sb + dd + SM_MEM + G * 4096 + wu * 256 + (tx & 31) * 8;
            const uint32_t qq = sb + SM_SC + ((tx >> 3) & 3) * 640 + (tx & 7) * 16;
            PIN2(qq, id)
            SCHED_FENCE
            bar_sync(NB_O, 384);
            uint32_t B[8];
            ldsm4t(B[0], B[1], B[2], B[3], qq);
            SCHED_FENCE
            ldsm4t(B[4], B[5], B[6], B[7], qq + 2560);
            SCHED_FENCE
            float c[4] = {0.f, 0.f, 0.f, 0.f}, c2[4] = {0.f, 0.f, 0.f, 0.f}, c3[4] = {0.f, 0.f, 0.f, 0.f}, c4[4] = {0.f, 0.f, 0.f, 0.f};
            MMA_K(c, A, 0) MMA_K(c2, A, 1) MMA_K(c3, A2, 0)
            SCHED_FENCE
            MMA_K(c, A, 2) MMA_K(c2, A, 3) MMA_K(c3, A2, 1)
            LD_T(&A3[0], oa + 2 * 8192) LD_T(&A3[4], oa + 2 * 8192 + 2048) LD_T(&A3[8], oa + 2 * 8192 + 2 * 2048)
            SCHED_FENCE
            MMA_K(c3, A2, 2)
            st_async2(id + 1024, pack_bf16(c[0] + c2[0], c[1] + c2[1]), pack_bf16(c[2] + c2[2], c[3] + c2[3]), ib);
            LD_T(&A3[12], oa + 2 * 8192 + 3 * 2048)
            SCHED_FENCE
            MMA_K(c3, A2, 3)
            st_async2(id + 2048, pack_bf16(c3[0], c3[1]), pack_bf16(c3[2], c3[3]), ib);
            SCHED_FENCE
            float c5[4] = {0.f, 0.f, 0.f, 0.f};
            MMA_K(c4, A3, 0) MMA_K(c5, A3, 1) MMA_K(c4, A3, 2) MMA_K(c5, A3, 3)
            st_async2(id + 3072, pack_bf16(c4[0] + c5[0], c4[1] + c5[1]), pack_bf16(c4[2] + c5[2], c4[3] + c5[3]), ib + 32);
            SCHED_FENCE
            asm volatile("cp.async.bulk.wait_group 0;" ::: "memory");
            mbar_wait(sb + SM_BAR + MB_G + 8 * G, (s + 1) & 1);
            bar_sync(NB_TS, 384);
        }
        token_gemm<G, false>(sb, W, QP, ta, s + 1, (opaque((int)mb) >> 4), wu);
    }
}

#define AG_WEAK 0
#define AG_OP "ld.relaxed.gpu.global.v4.u32"
__device__ __forceinline__ uint4 AG_LD(const void* p) {
    uint4 v; asm volatile(AG_OP " {%0,%1,%2,%3}, [%4];" : "=r"(v.x), "=r"(v.y), "=r"(v.z), "=r"(v.w) : "l"(p) : "memory"); return v;
}
__device__ __forceinline__ void ag_ld_if(uint4& v, const void* p, bool c) {
    asm volatile("{\n.reg .pred p;\nsetp.ne.u32 p, %5, 0;\n@p " AG_OP " {%0,%1,%2,%3}, [%4];\n}" : "+r"(v.x), "+r"(v.y), "+r"(v.z), "+r"(v.w) : "l"(p), "r"((uint32_t)c) : "memory");
}
__device__ __forceinline__ void sts128_if(uint32_t a, uint4 v, bool c) {
    asm volatile("{\n.reg .pred p;\nsetp.ne.u32 p, %5, 0;\n@p st.shared.v4.u32 [%0], {%1,%2,%3,%4};\n}" :: "r"(a), "r"(v.x), "r"(v.y), "r"(v.z), "r"(v.w), "r"((uint32_t)c) : "memory");
}
__device__ __forceinline__ bool rs_try(const uint32_t (&L)[8], uint32_t ntag, uint32_t atag, uint32_t keep, uint64_t pub, uint32_t idle) {
    const float lo = ((bf_lo(L[0]) + bf_lo(L[1])) + (bf_lo(L[2]) + bf_lo(L[3]))) + ((bf_lo(L[4]) + bf_lo(L[5])) + (bf_lo(L[6]) + bf_lo(L[7])));
    const float hi = ((bf_hi(L[0]) + bf_hi(L[1])) + (bf_hi(L[2]) + bf_hi(L[3]))) + ((bf_hi(L[4]) + bf_hi(L[5])) + (bf_hi(L[6]) + bf_hi(L[7])));
    const float l1 = __shfl_xor_sync(0xffffffffu, lo, 8), h1 = __shfl_xor_sync(0xffffffffu, hi, 8), l2 = __shfl_xor_sync(0xffffffffu, lo, 16);
    const float h2 = __shfl_xor_sync(0xffffffffu, hi, 16), l3 = __shfl_xor_sync(0xffffffffu, lo, 24), h3 = __shfl_xor_sync(0xffffffffu, hi, 24);
    const uint32_t bad = lop3<0xA8>(lop3<0xFE>(lop3<0x7E>(L[0], L[1], ntag), lop3<0x7E>(L[2], L[3], ntag), lop3<0x7E>(L[4], L[5], ntag)), lop3<0x7E>(L[6], L[7], ntag), 1u);
    const bool ok = __all_sync(0xffffffffu, bad == 0u);
    const uint32_t w = lop3<0xE4>(atag, pack_bf16((lo + l1) + (l2 + l3), (hi + h1) + (h2 + h3)), keep);
    asm volatile("{\n.reg .pred p, q;\nsetp.ne.u32 p, %0, 0;\nsetp.eq.and.u32 q, %3, 0, p;\n@q st.relaxed.gpu.global.u32 [%1], %2;\n}"
                 :: "r"((uint32_t)ok), "l"(pub), "r"(w), "r"(idle) : "memory");
    return ok;
}

__device__ __forceinline__ uint32_t hmul2(uint32_t a, uint32_t b) { uint32_t r; asm("mul.rn.bf16x2 %0, %1, %2;" : "=r"(r) : "r"(a), "r"(b)); return r; }
__device__ __forceinline__ void gate6(int tok0, int lane, const bf16* __restrict__ x, const bf16* __restrict__ gate_w) {
    uint2 u[6][5], g[5];
#pragma unroll
    for (int i = 0; i < 5; i++) asm volatile("ld.global.nc.v2.u32 {%0,%1}, [%2];" : "=r"(g[i].x), "=r"(g[i].y) : "l"(gate_w + lane * 4 + 128 * i));
#pragma unroll
    for (int j = 0; j < 6; j++)
#pragma unroll
        for (int i = 0; i < 5; i++)
            asm volatile("ld.global.nc.v2.u32 {%0,%1}, [%2];" : "=r"(u[j][i].x), "=r"(u[j][i].y) : "l"(x + (size_t)min(tok0 + j, S_LEN - 1) * DM + lane * 4 + 128 * i));
    asm volatile("" ::: "memory");
    float mine = 0.f;
#pragma unroll
    for (int j = 0; j < 6; j++) {
        float c[4] = {0.f, 0.f, 0.f, 0.f};
#pragma unroll
        for (int i = 0; i < 5; i++) mma16816(c, 0x3F803F80u, 0x3F803F80u, 0x3F803F80u, 0x3F803F80u, hmul2(u[j][i].x, g[i].x), hmul2(u[j][i].y, g[i].y));
        float a = c[0] + c[1];
        a += __shfl_xor_sync(0xffffffffu, a, 1); a += __shfl_xor_sync(0xffffffffu, a, 2);
        if (lane == j) mine = a;
    }
    if (lane < 6 && tok0 + lane < S_LEN) {
        const float a = __bfloat162float(__float2bfloat16(mine));
        g_gate[tok0 + lane] = __bfloat162float(__float2bfloat16(1.f / (1.f + __expf(-a))));
    }
}

__device__ __forceinline__ void rec_comm(uint32_t sb, uint32_t rank, const CUtensorMap* tm_x, int head, const bf16* x, const bf16* gate_w) {
    const uint32_t d1 = (rank == 2 ? -2 : 1) << 24, d2 = (rank == 0 ? 2 : -1) << 24;
    const int tid = tid_pinned() - 256, lane = tid & 31;
    const int v = __shfl_sync(0xffffffffu, (int)(threadIdx.x >> 5) & 3, 0);
    const uint32_t ep = get_epoch();
    gate6((blockIdx.x * 4 + v) * 6, lane, x, gate_w);
    const uint32_t epoch = __shfl_sync(0xffffffffu, ep, 0);
    const uint32_t own0 = v < 2 ? 0u : v - 1u;
    uint32_t selm = 0;
    uint32_t rx = 0, ax = 0;
    unsigned best = ~0u;
    if (lane < 8 && v < 2) st_relaxed1(rs_base() + (2 << 20) - 8192 + (v & 1) * 4096 + blockIdx.x * 32 + lane * 4, 0u);
    asm volatile("barrier.cluster.wait.acquire;" ::: "memory");
    const uint32_t glo0 = (uint32_t)(uintptr_t)rs_base(), ghi = (uint32_t)((uintptr_t)rs_base() >> 32);
    const uint32_t ro = glo0 + blockIdx.x * 8192, po = glo0 + ag_off(blockIdx.x >> 5, 0u) + (blockIdx.x & 31) * 128 + v * 32;
    const uint32_t ao0 = glo0 + ag_off(0, 0u), ao1 = glo0 + ag_off(1, 0u), ao2 = glo0 + ag_off(2, 0u);
    const bool mine0 = own0 == rank;
    const int tid0 = tid;
    constexpr int rs_at = RS_AT, ag_at = AG_AT;
    const unsigned ag_d = AG_D + ((blockIdx.x < 72 && blockIdx.x % 24 >= 16) ? 0 : AG_E);
    int err = 0;
    uint32_t A[16];
#define ISSUE_X(seg) { if (v >= 2) { if (X_AT) spin_until(clk32(), X_AT); if (elect_one()) issue_x(sb, tm_x, seg, v & 1); __syncwarp(); } }
    bar_sync(NB_ALL, 384);
    ISSUE_X(1)
    for (int s = 0; s < NSEG; s++) {
        const int tid = opaque(tid0), lane = tid & 31;
        const uint32_t par = (s & 1) + (tid >> 10);
        const uint32_t t8 = sb + (lane & 7) * 16, qq = t8 + SM_SC + (lane >> 3) * 640;
        const uint32_t xb = sb + SM_BAR + MB_X;
        if (s <= SW_AT) {
            if (s < SW_AT && lane == 0) {
                unsigned dt;
                asm volatile("{ .reg .pred q; .reg .u32 o, a, b;\nmov.u32 a, %%clock;\natom.relaxed.gpu.global.exch.b32 o, [%1], 2;\n"
                             "and.b32 o, o, 1;\nsetp.eq.u32 q, o, 0;\nmov.u32 b, 0;\n@q mov.u32 b, %%clock;\nsub.u32 %0, b, a; }"
                             : "=r"(dt) : "l"(rs_base() + (2 << 20) - 8192 + (v & 1) * 4096 + blockIdx.x * 32) : "memory");
                best = min(best, dt);
                sts32(sb + SM_PB + v * 4, best);
            }
            if (s == 0 && tid == 0) asm volatile("red.release.gpu.global.add.u32 [%0], %1;" :: "l"(&g_ctl.gate), "r"(blockIdx.x < 32 ? 8u : 4u) : "memory");
            __syncwarp();
            if (s == SW_AT) {
                const int T = (lane >> 1) == 0 ? 36 + v : 12 * rank + 4 * ((lane >> 1) - 1) + v, r = lane < 8 ? 2 * T + (lane & 1) : blockIdx.x;
                const uint32_t sd = get_side(r, epoch);
                const uint32_t m = __ballot_sync(0xffffffffu, (rs_off(r, sd) >> 12) & 1u);
                selm = m & 255u; rx = (m & 256u) << 4; ax = __shfl_sync(0xffffffffu, sd, 8) << 12;
            }
        }
        const uint32_t glo = glo0 + v * 16384 + (lane >> 3) * 1024 + head * 32 + (lane & 7) * 4;
#define RS_AD(i, h) mk64(((i) == 0 ? glo : glo + rank * (24 * 8192)) + (((selm >> (2 * (i) + (h))) & 1u) << 12), ghi)
#define RS_OF(i, h) (((i) == 0 ? 72 : 8 * ((i) - 1)) * 8192 + (h) * 8192)
        if (s == NSEG - 1) {
            if (mine0) { st_relaxed1_a<RS_OF(0, 0)>(RS_AD(0, 0), 0u); st_relaxed1_a<RS_OF(0, 1)>(RS_AD(0, 1), 0u); }
            st_relaxed1_a<RS_OF(1, 0)>(RS_AD(1, 0), 0u); st_relaxed1_a<RS_OF(1, 1)>(RS_AD(1, 1), 0u); st_relaxed1_a<RS_OF(2, 0)>(RS_AD(2, 0), 0u);
            st_relaxed1_a<RS_OF(2, 1)>(RS_AD(2, 1), 0u); st_relaxed1_a<RS_OF(3, 0)>(RS_AD(3, 0), 0u); st_relaxed1_a<RS_OF(3, 1)>(RS_AD(3, 1), 0u);
            if (v == 0) bar_sync(NB_X0, 288); else bar_sync(NB_XR, 352);
            bar_arrive(NB_QK, 384);
            break;
        }
        if (v == 1) {
            if (lane < 9) mbar_expect(lane == 8 ? xb : sb + SM_IB + lane * 8, lane == 8 ? 1920u : lane >= 4 ? 512u : (lane < 2 ? 0u : lane - 1u) == rank ? 1536u : 1024u);
            __syncwarp();
        }
        const uint32_t xi = sb + SM_XIN + lane * 16, l4 = sb + lane * 4 + v * 1280;
        const uint32_t vp = t8 + v * 1280 + ((lane >> 3) & 1) * 640 + ((lane >> 4) ? SM_SC + 384 : SM_VB + 512);
        const uint32_t vx = t8 + SM_VB + v * 1280 + ((lane >> 3) & 1) * 640 + (lane >> 4) * 128;
        PIN2(vx, vp)
        if (v == 0) {
            SCHED_FENCE
            bar_sync(NB_X0, 288);
        } else {
            uint32_t ka[16], qb[8], qc[8];
            float s0[4] = {0.f, 0.f, 0.f, 0.f}, s1[4] = {0.f, 0.f, 0.f, 0.f}, s2[4] = {0.f, 0.f, 0.f, 0.f}, s3[4] = {0.f, 0.f, 0.f, 0.f};
            const uint32_t xo = sb + SM_XIN + rank * 640 + (v - 1) * 256 + lane * 4;
            const uint32_t x1 = xo + d1, x2 = xo + d2, b1 = xb + d1 + (tid >> 10), b2 = xb + d2 + (tid >> 10), b0 = xb + (tid >> 10);
            PIN2(x1, x2) PIN2(b1, b2) PIN2(xo, b0)
#define SC_MMA \
            mma16816(s0, ka[0], ka[1], ka[2], ka[3], qb[0], qb[1]); SCHED_FENCE mma16816(s1, ka[4], ka[5], ka[6], ka[7], qb[2], qb[3]); SCHED_FENCE \
            mma16816(s2, ka[0], ka[1], ka[2], ka[3], qc[0], qc[1]); SCHED_FENCE mma16816(s3, ka[4], ka[5], ka[6], ka[7], qc[2], qc[3]); SCHED_FENCE \
            mma16816(s0, ka[8], ka[9], ka[10], ka[11], qb[4], qb[5]); SCHED_FENCE mma16816(s1, ka[12], ka[13], ka[14], ka[15], qb[6], qb[7]); SCHED_FENCE \
            mma16816(s2, ka[8], ka[9], ka[10], ka[11], qc[4], qc[5]); SCHED_FENCE mma16816(s3, ka[12], ka[13], ka[14], ka[15], qc[6], qc[7]); SCHED_FENCE
            if (v < 3) {
                const uint32_t aa = t8 + SM_KB + (lane >> 4) * 640 + ((lane >> 3) & 1) * 128 + (v - 1) * 256;
#pragma unroll
                for (int ks = 0; ks < 4; ks++) LD_T(&ka[4 * ks], aa + ks * 1280)
                SCHED_FENCE
                bar_sync(NB_XR, 352);
                LD_T(&qb[0], qq) SCHED_FENCE LD_T(&qc[0], qq + 128) SCHED_FENCE LD_T(&qb[4], qq + 2560) SCHED_FENCE LD_T(&qc[4], qq + 2560 + 128)
                SCHED_FENCE
                SC_MMA
                const uint32_t q0 = pack_bf16((s0[0] + s1[0]) + (s2[0] + s3[0]), (s0[1] + s1[1]) + (s2[1] + s3[1]));
                const uint32_t q1 = pack_bf16((s0[2] + s1[2]) + (s2[2] + s3[2]), (s0[3] + s1[3]) + (s2[3] + s3[3]));
                st_async1(x1, q0, b1); st_async1(x2, q0, b2); st_async1(x1 + 128, q1, b1); st_async1(x2 + 128, q1, b2);
                st_async1(xo, q0, b0); st_async1(xo + 128, q1, b0);
            } else {
                const uint32_t aa = t8 + (lane >> 4) * 640 + (((lane >> 3) & 1) ? SM_SC + 256 : SM_KB + 512);
                PIN1(aa)
                SCHED_FENCE
                bar_sync(NB_XR, 352);
                LD_T(&ka[0], aa) SCHED_FENCE LD_T(&qb[0], qq) SCHED_FENCE LD_T(&ka[4], aa + 1280) SCHED_FENCE LD_T(&qc[0], qq + 128) SCHED_FENCE
                LD_T(&ka[8], aa + 2 * 1280) SCHED_FENCE LD_T(&qb[4], qq + 2560) SCHED_FENCE LD_T(&ka[12], aa + 3 * 1280) SCHED_FENCE LD_T(&qc[4], qq + 2560 + 128)
                SCHED_FENCE
                SC_MMA
                const uint32_t q0 = pack_bf16((((s0[0] + s0[2]) + (s1[0] + s1[2])) + (s2[0] + s2[2])) + (s3[0] + s3[2]), (((s0[1] + s0[3]) + (s1[1] + s1[3])) + (s2[1] + s2[3])) + (s3[1] + s3[3]));
                st_async1(x1, q0, b1); st_async1(x2, q0, b2); st_async1(xo, q0, b0);
            }
#undef SC_MMA
        }
        uint32_t va[8], vm[4];
        ldsm4(va[0], va[1], va[2], va[3], vx);
        ldsm4(va[4], va[5], va[6], va[7], vx + 256);
        ldsm4(vm[0], vm[1], vm[2], vm[3], vp);
        bar_arrive(NB_QK, 384);
        const uint32_t oa = sb + SM_WO + ((lane >> 4) * 8 + (lane & 7)) * 128 + (((2 * v + ((lane >> 3) & 1)) ^ (lane & 7)) << 4);
        if (s == 0) { mbar_wait(sb + SM_BAR + MB_W2, 0); LD_O(A, oa + 9 * 8192) }
        uint32_t pb[5];
        const uint32_t ow = oa + rank * (3 * 8192);
        const uint32_t dd = (own0 - rank) << 24;
        const uint32_t id = sb + dd + SM_MEM + ((own0 + 2u - rank) % 3u) * 4096 + v * 256 + lane * 8, ib = sb + dd + SM_IB + v * 8 + (tid >> 10);
        {
            PIN2(ow, id) PIN1(ib) PIN2(xi, l4)
            SCHED_FENCE
            mbar_wait(xb, s & 1);
            uint32_t u[16];
            LD_T(&u[0], xi) LD_T(&u[4], xi + 512) LD_T(&u[8], xi + 1024) LD_T(&u[12], xi + 1536)
            float p[10];
#pragma unroll
            for (int n = 0; n < 5; n++) {
                p[2 * n] = bf_lo(u[n]) + bf_lo(u[5 + n]) + bf_lo(u[10 + n]);
                p[2 * n + 1] = bf_hi(u[n]) + bf_hi(u[5 + n]) + bf_hi(u[10 + n]);
            }
            const float ml = fmaxf(fmaxf(fmaxf(fmaxf(p[0], p[1]), fmaxf(p[2], p[3])), fmaxf(p[4], p[5])), fmaxf(fmaxf(p[6], p[7]), fmaxf(p[8], p[9])));
            const float m1 = __shfl_xor_sync(0xffffffffu, ml, 1), m2 = __shfl_xor_sync(0xffffffffu, ml, 2), m3 = __shfl_xor_sync(0xffffffffu, ml, 3);
            const float mb = ml * SCALE_A;
#pragma unroll
            for (int i = 0; i < 10; i++) p[i] = ex2(fmaf(p[i], SCALE_A, -mb));
            const float cr = ex2(fmaf(fmaxf(fmaxf(ml, m1), fmaxf(m2, m3)), -SCALE_A, mb));
#pragma unroll
            for (int i = 0; i < 5; i++) pb[i] = pack_bf16(p[2 * i] * cr, p[2 * i + 1] * cr);
            float o[4] = {0.f, 0.f, 0.f, 0.f}, o2[4] = {0.f, 0.f, 0.f, 0.f};
            mma16816(o, va[0], va[1], va[2], va[3], pb[0], pb[1]);
            mma16816(o2, va[4], va[5], va[6], va[7], pb[2], pb[3]);
            mma16816(o, vm[0], vm[1], vm[2], vm[3], pb[4], pb[4]);
            sts32(l4 + SM_SC, pack_bf16(o[0] + o2[0], o[1] + o2[1]));
            sts32(l4 + SM_SC + 640, pack_bf16(o[2] + o2[2], o[3] + o2[3]));
        }
        SCHED_FENCE
        bar_sync(NB_O, 384);
        const unsigned t_o = clk32() + (lane >> 16);
        {
            float z[4] = {0.f, 0.f, 0.f, 0.f}, z2[4] = {0.f, 0.f, 0.f, 0.f}, z3[4] = {0.f, 0.f, 0.f, 0.f};
            mma16816(z, 0x3F803F80u, 0x3F803F80u, 0x3F803F80u, 0x3F803F80u, pb[0], pb[1]);
            mma16816(z2, 0x3F803F80u, 0x3F803F80u, 0x3F803F80u, 0x3F803F80u, pb[2], pb[3]);
            mma1688(z3, 0x3F803F80u, 0x3F803F80u, pb[4]);
            SCHED_FENCE
            uint32_t B[8], A2[16], A3[16], A4[16];
            const float i0 = rcp(z[0] + z2[0] + z3[0]), i1 = rcp(z[1] + z2[1] + z3[1]);
            asm volatile("" :: "f"(i0), "f"(i1));
            SCHED_FENCE
            ldsm4t(B[0], B[1], B[2], B[3], qq);
            SCHED_FENCE
            ldsm4t(B[4], B[5], B[6], B[7], qq + 2560);
            SCHED_FENCE
            float f[4][4], c2[4] = {0.f, 0.f, 0.f, 0.f};
#pragma unroll
            for (int i = 0; i < 4; i++) { f[i][0] = f[i][1] = f[i][2] = f[i][3] = 0.f; }
#define LD_W(P, i, ks) LD_T(&P[4 * (ks)], ow + (i) * 8192 + (ks) * 2048) SCHED_FENCE
#define MM_W(P, i, ks) MMA_K(f[(i) + 1], P, ks) SCHED_FENCE
            MMA_K(f[0], A, 0) MMA_K(c2, A, 1)
            SCHED_FENCE
            MMA_K(f[0], A, 2) MMA_K(c2, A, 3)
            SCHED_FENCE
            LD_W(A2, 0, 0) LD_W(A3, 1, 0) LD_W(A4, 2, 0) LD_W(A2, 0, 1) LD_W(A3, 1, 1) LD_W(A4, 2, 1)
            f[0][0] += c2[0]; f[0][1] += c2[1]; f[0][2] += c2[2]; f[0][3] += c2[3];
            asm volatile("{\n.reg .pred p;\nsetp.eq.u32 p, %4, 0;\n@p st.async.weak.shared::cluster.mbarrier::complete_tx::bytes.v2.b32 [%0], {%1,%2}, [%3];\n}"
                         :: "r"(id), "r"(pack_bf16(f[0][0], f[0][1])), "r"(pack_bf16(f[0][2], f[0][3])), "r"(ib), "r"((uint32_t)mine0 + (tid >> 10)) : "memory");
            SCHED_FENCE
            LD_W(A2, 0, 2) LD_W(A3, 1, 2)
            MM_W(A2, 0, 0) MM_W(A3, 1, 0) MM_W(A4, 2, 0)
            MM_W(A2, 0, 1) LD_W(A4, 2, 2) MM_W(A3, 1, 1) LD_W(A2, 0, 3) MM_W(A4, 2, 1) LD_W(A3, 1, 3)
            MM_W(A2, 0, 2) LD_W(A4, 2, 3) MM_W(A3, 1, 2) MM_W(A4, 2, 2)
            MM_W(A2, 0, 3) MM_W(A3, 1, 3) MM_W(A4, 2, 3)
#undef LD_W
#undef MM_W
            const uint64_t g00 = RS_AD(0, 0), g01 = RS_AD(0, 1), g10 = RS_AD(1, 0), g11 = RS_AD(1, 1), g20 = RS_AD(2, 0), g21 = RS_AD(2, 1), g30 = RS_AD(3, 0), g31 = RS_AD(3, 1);
            PINL(g00) PINL(g01) PINL(g10) PINL(g11) PINL(g20) PINL(g21) PINL(g30) PINL(g31)
            const uint32_t tag = par ^ 1u, in = sb + SM_MEM + v * 256 + lane * 8;
            const uint32_t eye = ((lane >> 2) == 2 * (lane & 3) ? 0x3F80u : 0u) | ((lane >> 2) == 2 * (lane & 3) + 1 ? 0x3F800000u : 0u);
            PIN2(tag, in) PIN1(eye)
#define O_LD(i) const uint2 x##i = lds64(in + (i) * 1024), y##i = lds64(in + (i) * 1024 + 4096);
#define O_ADD(i) mma16816(f[i], x##i.x, x##i.y, y##i.x, y##i.y, eye, eye);
#define O_PUT(i) { st_relaxed1_a<RS_OF(i, 0)>(g##i##0, lop3<0xE4>(tag, pack_bf16(f[i][0] * i0, f[i][1] * i1), 1u)); \
                   st_relaxed1_a<RS_OF(i, 1)>(g##i##1, lop3<0xE4>(tag, pack_bf16(f[i][2] * i0, f[i][3] * i1), 1u)); }
            SCHED_FENCE
            mbar_wait(sb + SM_IB + v * 8, s & 1);
            O_LD(1) O_LD(2) O_LD(0)
            O_ADD(1) O_ADD(2) O_ADD(0)
            uint32_t okb;
            asm volatile("{\n.reg .pred p;\nmbarrier.try_wait.parity.shared::cta.b64 p, [%1], %2;\nselp.u32 %0, 1, 0, p;\n}" : "=r"(okb) : "r"(sb + SM_IB + 32 + v * 8), "r"(s & 1) : "memory");
            O_PUT(1) O_PUT(2)
            asm volatile("{\n.reg .pred p;\nsetp.ne.u32 p, %4, 0;\n@p st.relaxed.gpu.global.u32 [%0 + %5], %2;\n@p st.relaxed.gpu.global.u32 [%1 + %6], %3;\n}"
                         :: "l"(g00), "l"(g01), "r"(lop3<0xE4>(tag, pack_bf16(f[0][0] * i0, f[0][1] * i1), 1u)), "r"(lop3<0xE4>(tag, pack_bf16(f[0][2] * i0, f[0][3] * i1), 1u)),
                            "r"((uint32_t)mine0 + (tid >> 10)), "n"(RS_OF(0, 0)), "n"(RS_OF(0, 1)) : "memory");
            asm volatile("{\n.reg .pred p;\n.reg .u32 n;\nsetp.ne.u32 p, %2, 0;\n@p bra.uni FD_%=;\nmov.u32 n, 0;\n"
                         "FL_%=:\nmbarrier.try_wait.parity.shared::cta.b64 p, [%0], %1;\n@p bra.uni FD_%=;\n"
                         "add.u32 n, n, 1;\nsetp.lt.u32 p, n, %3;\n@p bra.uni FL_%=;\nFD_%=:\n}"
                         :: "r"(sb + SM_IB + 32 + v * 8), "r"(s & 1), "r"(okb), "n"(SPIN_MAX) : "memory");
            O_LD(3) O_ADD(3) O_PUT(3)
#undef O_LD
#undef O_ADD
#undef O_PUT
            bar_arrive(NB_TS, 384);
        }
#undef RS_AD
#undef RS_OF
        bar_sync(NB_WG2, 128);
        const int tq = opaque(tid0);
        const uint32_t ntag = par - 1u;
        const uint32_t atag = ntag ^ epoch;
        if (s == SW_AT - 1 && tq < 8) {
            const uint4 b = lds128(sb + SM_PB);
            st_relaxed1(&g_side[blockIdx.x * 8 + tq], ((epoch + 1) << 1) | hashbit((2 << 20) - 8192 + (min(b.y, b.w) < min(b.x, b.z)) * 4096));
        }
        __syncwarp();
        const unsigned cold = s == SW_AT ? COLD_D : 0;
        unsigned t_a = t_o + ag_at + cold;
        if (__builtin_expect(blockIdx.x < NRED, 1)) {
            const char* q0 = (const char*)mk64((ro ^ rx) + v * 1024 + (tq & 31) * 4, ghi);
            constexpr int ST = 128;
            const uint64_t pub = mk64((po + (tq & 7) * 4) ^ ((tq & 8) << 9), ghi);
            const uint32_t keep = (tq & 3) == 0 ? 1u : 0u;
            PINL(q0) PINL(pub) PIN2(ntag, keep)
#define RS_LD(L, q) { L[0] = ld_relaxed1_off<0>(q); L[1] = ld_relaxed1_off<ST>(q); L[2] = ld_relaxed1_off<2 * ST>(q); L[3] = ld_relaxed1_off<3 * ST>(q); \
                      L[4] = ld_relaxed1_off<4 * ST>(q); L[5] = ld_relaxed1_off<5 * ST>(q); L[6] = ld_relaxed1_off<6 * ST>(q); L[7] = ld_relaxed1_off<7 * ST>(q); }
            spin_until(t_o, rs_at + cold);
            int n = 0;
#pragma unroll 1
            while (true) {
                uint32_t L[8], M[8];
                RS_LD(L, q0)
                uint32_t ql = __shfl_sync(0xffffffffu, (uint32_t)(uintptr_t)q0, tq);
#pragma unroll
                for (int i = 0; i < RS_CH; i++) asm volatile("brev.b32 %0, %0;\nbrev.b32 %0, %0;" : "+r"(ql));
                const char* q1 = (const char*)mk64(ql, ghi);
                RS_LD(M, q1)
                if (rs_try(L, ntag, atag, keep, pub, tq & 16)) break;
                n++;
                if (rs_try(M, ntag, atag, keep, pub, tq & 16) || ++n > SPIN_MAX / 64) break;
            }
            if (PAUSE) bar_arrive(NB_PUB, 384);
            t_a = clk32() + ag_d;
#undef RS_LD
            err |= n;
        } else if (PAUSE) {
            bar_arrive(NB_PUB, 384);
        }
        const char* a0 = (const char*)mk64((ao0 ^ ax) + tq * 16, ghi);
        const char* a1 = (const char*)mk64((ao1 ^ ax) + tq * 16, ghi);
        const char* a2 = (const char*)mk64((ao2 ^ ax) + tq * 16, ghi);
        const uint32_t md = sb + SM_MEM + tq * 16;
        PINL(a0) PINL(a1) PINL(a2) PIN1(md)
        spin_until(t_o, t_a - t_o);
        {
            int n = 0;
            uint4 w0 = AG_LD(a0), w1 = AG_LD(a0 + 2048), w2 = AG_LD(a1), w3 = AG_LD(a1 + 2048), w4 = AG_LD(a2);
            sts128(md, w0); sts128(md + 2048, w1); sts128(md + 4096, w2); sts128(md + 6144, w3); sts128(md + 8192, w4);
#pragma unroll 1
            while (__builtin_expect(__any_sync(0xffffffffu, lop3<0xA8>(lop3<0x7E>(w0.x, w1.x, atag) | lop3<0x7E>(w2.x, w3.x, atag), w4.x ^ atag, 1u) != 0u), 0) && ++n <= SPIN_MAX / 64) {
                const bool b0 = (w0.x ^ atag) & 1u, b1 = (w1.x ^ atag) & 1u, b2 = (w2.x ^ atag) & 1u, b3 = (w3.x ^ atag) & 1u, b4 = (w4.x ^ atag) & 1u;
                ag_ld_if(w0, a0, b0); ag_ld_if(w1, a0 + 2048, b1); ag_ld_if(w2, a1, b2); ag_ld_if(w3, a1 + 2048, b3); ag_ld_if(w4, a2, b4);
                sts128_if(md, w0, b0); sts128_if(md + 2048, w1, b1); sts128_if(md + 4096, w2, b2); sts128_if(md + 6144, w3, b3); sts128_if(md + 8192, w4, b4);
            }
            err |= n;
        }
        bar_sync(NB_ALL, 384);
        if (s + 2 < NSEG) ISSUE_X(s + 2)
        if (v == 0 && s > 0 && ((s & 3) == 0 || s == NSEG - 2)) {
            if (elect_one()) {
                asm volatile("red.relaxed.gpu.global.add.u32 [%0], 2;" :: "l"(&g_ctl.seg[(s >> 1) - 1]) : "memory");
                if (!(s & 2)) asm volatile("red.relaxed.gpu.global.add.u32 [%0], 2;" :: "l"(&g_ctl.seg[(s >> 1) - 2]) : "memory");
            }
            __syncwarp();
        }
    }
    if (err > SPIN_MAX / 64) g_err = 3;
}

__global__ void __cluster_dims__(3, 1, 1) __launch_bounds__(384, 1)
rec_kernel(const __grid_constant__ CUtensorMap tm_x, const __grid_constant__ CUtensorMap tm_wq, const __grid_constant__ CUtensorMap tm_wk,
           const __grid_constant__ CUtensorMap tm_wv, const __grid_constant__ CUtensorMap tm_wo, const bf16* __restrict__ mem0,
           const bf16* __restrict__ x, const bf16* __restrict__ gate_w) {
    extern __shared__ __align__(1024) char smem_raw[];
    const uint32_t sb = smem_u32(smem_raw);
    uint32_t rank; asm volatile("mov.u32 %0, %%cluster_ctarank;" : "=r"(rank));
    const int head = blockIdx.x / 3;
    asm volatile("griddepcontrol.launch_dependents;" ::: "memory");
    const int wid = __shfl_sync(0xffffffffu, (int)(threadIdx.x >> 5), 0), wg = wid >> 2;
    if (wid == 0) {
        if (elect_one()) {
            if ((sb & 0x3FFFF) != SB0 || mapa(sb, 0) + (rank << 24) != sb || mapa(sb, 2) - mapa(sb, 1) != (1u << 24)) __trap();
            mbar_init(sb + SM_BAR + MB_W0, 1); mbar_init(sb + SM_BAR + MB_W1, 1); mbar_init(sb + SM_BAR + MB_W2, 1);
            mbar_init(sb + SM_BAR + MB_G, 1); mbar_init(sb + SM_BAR + MB_G + 8, 1); mbar_init(sb + SM_BAR + MB_X, 1);
#pragma unroll
            for (int i = 0; i < 8; i++) mbar_init(sb + SM_IB + 8 * i, 1);
            asm volatile("fence.mbarrier_init.release.cluster;" ::: "memory");
            fence_async_smem();
            mbar_expect(sb + SM_BAR + MB_W0, 163840);
            const uint64_t pol = pol_stream();
            issue_x(sb, &tm_x, 0, 0); issue_x(sb, &tm_x, 0, 1);
#pragma unroll
            for (int i = 0; i < 5; i++) {
                tma2d_s(sb + SM_WO + i * 16384, &tm_wk, head * DH + rank * 64, i * 128, sb + SM_BAR + MB_W0, pol);
                tma2d_s(sb + SM_WQ + i * 16384, &tm_wv, head * DH + rank * 64, i * 128, sb + SM_BAR + MB_W0, pol);
            }
#pragma unroll
            for (int i = 0; i < 5; i++) tma2d_prefetch(&tm_wq, head * DH + rank * 64, i * 128);
#pragma unroll
            for (int i = 0; i < 10; i++) tma2d_prefetch(&tm_wo, i * 64, head * DH + rank * 64);
        }
        __syncwarp();
    } else if (threadIdx.x >= 128 && threadIdx.x < 208) {
        const int c = threadIdx.x - 128;
        uint4 r[8];
#pragma unroll
        for (int i = 0; i < 8; i++) r[i] = __ldg((const uint4*)(mem0 + i * DM) + c);
#define MEM_COL(j, f, sel) sts128(sb + SM_MEM + (c * 8 + (j)) * 16, make_uint4(__byte_perm(r[0].f, r[1].f, sel), __byte_perm(r[2].f, r[3].f, sel), __byte_perm(r[4].f, r[5].f, sel), __byte_perm(r[6].f, r[7].f, sel)));
        MEM_COL(0, x, 0x5410) MEM_COL(1, x, 0x7632) MEM_COL(2, y, 0x5410) MEM_COL(3, y, 0x7632)
        MEM_COL(4, z, 0x5410) MEM_COL(5, z, 0x7632) MEM_COL(6, w, 0x5410) MEM_COL(7, w, 0x7632)
#undef MEM_COL
    }
    __syncwarp();
    asm volatile("barrier.cluster.arrive.relaxed;" ::: "memory");
    if (wg == 0) {
        bar_sync(NB_TA, 256);
        asm volatile("setmaxnreg.inc.sync.aligned.u32 %0;" :: "n"(R_WG0));
        rec_weights<0>(sb, rank, &tm_x, &tm_wq, &tm_wo, head);
        cluster_sync();
    } else if (wg == 1) {
        bar_sync(NB_TA, 256);
        asm volatile("setmaxnreg.inc.sync.aligned.u32 %0;" :: "n"(R_WG0));
        rec_weights<1>(sb, rank, &tm_x, &tm_wq, &tm_wo, head);
        cluster_sync();
    } else {
        asm volatile("setmaxnreg.dec.sync.aligned.u32 %0;" :: "n"(R_WG2));
        rec_comm(sb, rank, &tm_x, head, x, gate_w);
        cluster_sync();
    }
}

#define B_AHEAD 3
#define PF_AHEAD 14
#define EVF 15
#define REQ_AHEAD 7
constexpr uint32_t RING_CAP = 176 * 1024;
constexpr uint32_t SZ_O = 28672, SZ_Q = 40960, SZ_KV = 30720, SZ_B = 27648, SZ_QP = 49152;
#define QPRE 15
constexpr uint32_t G_OUT = RING_CAP, STG_BYTES = 24576;
constexpr uint32_t GEMM_SMEM = G_OUT + 2 * STG_BYTES + 512;

#define ACC64(d) ACC16(d), ACC16((d + 16)), ACC16((d + 32)), ACC16((d + 48))
__device__ __forceinline__ void wgmma_ss_n128_tb(float* d, uint64_t da, uint64_t db, int acc) {
    asm volatile("{\n.reg .pred p;\nsetp.ne.b32 p, %66, 0;\n"
                 "wgmma.mma_async.sync.aligned.m64n128k16.f32.bf16.bf16 "
                 "{%0,%1,%2,%3,%4,%5,%6,%7,%8,%9,%10,%11,%12,%13,%14,%15,%16,%17,%18,%19,%20,%21,%22,%23,%24,%25,%26,%27,%28,%29,%30,%31,"
                 "%32,%33,%34,%35,%36,%37,%38,%39,%40,%41,%42,%43,%44,%45,%46,%47,%48,%49,%50,%51,%52,%53,%54,%55,%56,%57,%58,%59,%60,%61,%62,%63}, "
                 "%64, %65, p, 1, 1, 0, 1;\n}"
                 : ACC64(d) : "l"(da), "l"(db), "r"(acc));
}

__device__ __forceinline__ void wgmma_ss_n192_tb(float* d, uint64_t da, uint64_t db, int acc) {
    asm volatile("{\n.reg .pred p;\nsetp.ne.b32 p, %98, 0;\n"
                 "wgmma.mma_async.sync.aligned.m64n192k16.f32.bf16.bf16 "
                 "{%0,%1,%2,%3,%4,%5,%6,%7,%8,%9,%10,%11,%12,%13,%14,%15,%16,%17,%18,%19,%20,%21,%22,%23,%24,%25,%26,%27,%28,%29,%30,%31,"
                 "%32,%33,%34,%35,%36,%37,%38,%39,%40,%41,%42,%43,%44,%45,%46,%47,%48,%49,%50,%51,%52,%53,%54,%55,%56,%57,%58,%59,%60,%61,%62,%63,"
                 "%64,%65,%66,%67,%68,%69,%70,%71,%72,%73,%74,%75,%76,%77,%78,%79,%80,%81,%82,%83,%84,%85,%86,%87,%88,%89,%90,%91,%92,%93,%94,%95}, "
                 "%96, %97, p, 1, 1, 0, 1;\n}"
                 : ACC64(d), ACC16((d + 64)), ACC16((d + 80)) : "l"(da), "l"(db), "r"(acc));
}

__device__ __forceinline__ void wgmma_ss_n128_tb_first(float* d, uint64_t da, uint64_t db) {
    asm volatile("wgmma.mma_async.sync.aligned.m64n128k16.f32.bf16.bf16 {%0,%1,%2,%3,%4,%5,%6,%7,%8,%9,%10,%11,%12,%13,%14,%15,%16,%17,%18,%19,%20,%21,%22,%23,%24,%25,%26,%27,%28,%29,%30,%31,%32,%33,%34,%35,%36,%37,%38,%39,%40,%41,%42,%43,%44,%45,%46,%47,%48,%49,%50,%51,%52,%53,%54,%55,%56,%57,%58,%59,%60,%61,%62,%63}, %64, %65, 0, 1, 1, 0, 1;"
                 : "=f"(d[0]), "=f"(d[1]), "=f"(d[2]), "=f"(d[3]), "=f"(d[4]), "=f"(d[5]), "=f"(d[6]), "=f"(d[7]), "=f"(d[8]), "=f"(d[9]), "=f"(d[10]), "=f"(d[11]), "=f"(d[12]), "=f"(d[13]), "=f"(d[14]), "=f"(d[15]), "=f"(d[16]), "=f"(d[17]), "=f"(d[18]), "=f"(d[19]), "=f"(d[20]), "=f"(d[21]), "=f"(d[22]), "=f"(d[23]), "=f"(d[24]), "=f"(d[25]), "=f"(d[26]), "=f"(d[27]), "=f"(d[28]), "=f"(d[29]), "=f"(d[30]), "=f"(d[31]), "=f"(d[32]), "=f"(d[33]), "=f"(d[34]), "=f"(d[35]), "=f"(d[36]), "=f"(d[37]), "=f"(d[38]), "=f"(d[39]), "=f"(d[40]), "=f"(d[41]), "=f"(d[42]), "=f"(d[43]), "=f"(d[44]), "=f"(d[45]), "=f"(d[46]), "=f"(d[47]), "=f"(d[48]), "=f"(d[49]), "=f"(d[50]), "=f"(d[51]), "=f"(d[52]), "=f"(d[53]), "=f"(d[54]), "=f"(d[55]), "=f"(d[56]), "=f"(d[57]), "=f"(d[58]), "=f"(d[59]), "=f"(d[60]), "=f"(d[61]), "=f"(d[62]), "=f"(d[63]) : "l"(da), "l"(db));
}
__device__ __forceinline__ void wgmma_ss_n192_tb_first(float* d, uint64_t da, uint64_t db) {
    asm volatile("wgmma.mma_async.sync.aligned.m64n192k16.f32.bf16.bf16 {%0,%1,%2,%3,%4,%5,%6,%7,%8,%9,%10,%11,%12,%13,%14,%15,%16,%17,%18,%19,%20,%21,%22,%23,%24,%25,%26,%27,%28,%29,%30,%31,%32,%33,%34,%35,%36,%37,%38,%39,%40,%41,%42,%43,%44,%45,%46,%47,%48,%49,%50,%51,%52,%53,%54,%55,%56,%57,%58,%59,%60,%61,%62,%63,%64,%65,%66,%67,%68,%69,%70,%71,%72,%73,%74,%75,%76,%77,%78,%79,%80,%81,%82,%83,%84,%85,%86,%87,%88,%89,%90,%91,%92,%93,%94,%95}, %96, %97, 0, 1, 1, 0, 1;"
                 : "=f"(d[0]), "=f"(d[1]), "=f"(d[2]), "=f"(d[3]), "=f"(d[4]), "=f"(d[5]), "=f"(d[6]), "=f"(d[7]), "=f"(d[8]), "=f"(d[9]), "=f"(d[10]), "=f"(d[11]), "=f"(d[12]), "=f"(d[13]), "=f"(d[14]), "=f"(d[15]), "=f"(d[16]), "=f"(d[17]), "=f"(d[18]), "=f"(d[19]), "=f"(d[20]), "=f"(d[21]), "=f"(d[22]), "=f"(d[23]), "=f"(d[24]), "=f"(d[25]), "=f"(d[26]), "=f"(d[27]), "=f"(d[28]), "=f"(d[29]), "=f"(d[30]), "=f"(d[31]), "=f"(d[32]), "=f"(d[33]), "=f"(d[34]), "=f"(d[35]), "=f"(d[36]), "=f"(d[37]), "=f"(d[38]), "=f"(d[39]), "=f"(d[40]), "=f"(d[41]), "=f"(d[42]), "=f"(d[43]), "=f"(d[44]), "=f"(d[45]), "=f"(d[46]), "=f"(d[47]), "=f"(d[48]), "=f"(d[49]), "=f"(d[50]), "=f"(d[51]), "=f"(d[52]), "=f"(d[53]), "=f"(d[54]), "=f"(d[55]), "=f"(d[56]), "=f"(d[57]), "=f"(d[58]), "=f"(d[59]), "=f"(d[60]), "=f"(d[61]), "=f"(d[62]), "=f"(d[63]), "=f"(d[64]), "=f"(d[65]), "=f"(d[66]), "=f"(d[67]), "=f"(d[68]), "=f"(d[69]), "=f"(d[70]), "=f"(d[71]), "=f"(d[72]), "=f"(d[73]), "=f"(d[74]), "=f"(d[75]), "=f"(d[76]), "=f"(d[77]), "=f"(d[78]), "=f"(d[79]), "=f"(d[80]), "=f"(d[81]), "=f"(d[82]), "=f"(d[83]), "=f"(d[84]), "=f"(d[85]), "=f"(d[86]), "=f"(d[87]), "=f"(d[88]), "=f"(d[89]), "=f"(d[90]), "=f"(d[91]), "=f"(d[92]), "=f"(d[93]), "=f"(d[94]), "=f"(d[95]) : "l"(da), "l"(db));
}

__device__ __forceinline__ void mma16816_n(float* c, uint32_t a0, uint32_t a1, uint32_t a2, uint32_t a3, uint32_t b0, uint32_t b1) {
    asm("mma.sync.aligned.m16n8k16.row.col.f32.bf16.bf16.f32 {%0,%1,%2,%3}, {%4,%5,%6,%7}, {%8,%9}, {%0,%1,%2,%3};"
        : "+f"(c[0]), "+f"(c[1]), "+f"(c[2]), "+f"(c[3]) : "r"(a0), "r"(a1), "r"(a2), "r"(a3), "r"(b0), "r"(b1));
}
__device__ __forceinline__ void mma1688_n(float* c, uint32_t a0, uint32_t a1, uint32_t b0) {
    asm("mma.sync.aligned.m16n8k8.row.col.f32.bf16.bf16.f32 {%0,%1,%2,%3}, {%4,%5}, {%6}, {%0,%1,%2,%3};"
        : "+f"(c[0]), "+f"(c[1]), "+f"(c[2]), "+f"(c[3]) : "r"(a0), "r"(a1), "r"(b0));
}
constexpr uint32_t B_PITCH = 336;
__device__ __forceinline__ uint32_t lds32_n(uint32_t a) { uint32_t v; asm("ld.shared.u32 %0, [%1];" : "=r"(v) : "r"(a)); return v; }
__device__ __forceinline__ uint32_t lds16_n(uint32_t a) { unsigned short v; asm("ld.shared.u16 %0, [%1];" : "=h"(v) : "r"(a)); return v; }
template <bool EDGE>
__device__ __forceinline__ void attnB_scores(uint32_t dq, uint32_t dk, int i, int tok0, int lane, float g0, float g1, uint32_t (&pa)[8]) {
    const int g = lane >> 2, t = lane & 3;
    const uint32_t qa = dq + (16 * i + 14 + g) * B_PITCH + 4 * t;
    const uint32_t a0 = lds32_n(qa), a1 = lds32_n(qa + 8 * B_PITCH), a2 = lds32_n(qa + 16), a3 = lds32_n(qa + 8 * B_PITCH + 16);
    const uint32_t e0 = t < 2 ? lds32_n(qa + 32) : 0u, e1 = t < 2 ? lds32_n(qa + 8 * B_PITCH + 32) : 0u;
    float sc[4][4];
#pragma unroll
    for (int n = 0; n < 4; n++) {
        const uint32_t ka = dk + (16 * i + 8 * n + g) * B_PITCH + 4 * t;
        const uint32_t b0 = lds32_n(ka), b1 = lds32_n(ka + 16), b2 = t < 2 ? lds32_n(ka + 32) : 0u;
        sc[n][0] = sc[n][1] = sc[n][2] = sc[n][3] = 0.f;
        mma16816_n(sc[n], a0, a1, a2, a3, b0, b1);
        mma1688_n(sc[n], e0, e1, b2);
    }
    const int odd = g & 1, e = g - 2 * t - odd + 14;
    float v0[4], v1[4];
    float m0 = -3.0e38f, m1 = -3.0e38f;
#pragma unroll
    for (int n = 0; n < 4; n++) {
        const int d0 = e - 8 * n, d1 = d0 + 8;
        const bool ok0 = d0 >= 0 && d0 <= 14 && (!EDGE || tok0 + 16 * i + g - d0 >= 0), ok1 = d1 >= 0 && d1 <= 14 && (!EDGE || tok0 + 16 * i + g + 8 - d1 >= 0);
        v0[n] = ok0 ? (odd ? sc[n][1] : sc[n][0]) : -3.0e38f;
        v1[n] = ok1 ? (odd ? sc[n][3] : sc[n][2]) : -3.0e38f;
        m0 = fmaxf(m0, v0[n]); m1 = fmaxf(m1, v1[n]);
    }
    m0 = fmaxf(m0, __shfl_xor_sync(0xffffffffu, m0, 1)); m1 = fmaxf(m1, __shfl_xor_sync(0xffffffffu, m1, 1));
    m0 = fmaxf(m0, __shfl_xor_sync(0xffffffffu, m0, 2)); m1 = fmaxf(m1, __shfl_xor_sync(0xffffffffu, m1, 2));
    const float scl = 0.22360679774997896f * 1.4426950408889634f;
    m0 *= scl; m1 *= scl;
    float s0 = 0.f, s1 = 0.f;
#pragma unroll
    for (int n = 0; n < 4; n++) {
        v0[n] = ex2(fmaf(fmaxf(v0[n], -1.0e30f), scl, -m0)); v1[n] = ex2(fmaf(fmaxf(v1[n], -1.0e30f), scl, -m1));
        s0 += v0[n]; s1 += v1[n];
    }
    s0 += __shfl_xor_sync(0xffffffffu, s0, 1); s1 += __shfl_xor_sync(0xffffffffu, s1, 1);
    s0 += __shfl_xor_sync(0xffffffffu, s0, 2); s1 += __shfl_xor_sync(0xffffffffu, s1, 2);
    const float i0 = rcp(s0) * g0, i1 = rcp(s1) * g1;
    const int sh = odd * 16;
#pragma unroll
    for (int k = 0; k < 2; k++) {
        pa[4 * k] = (pack_bf16(v0[2 * k] * i0, 0.f) & 0xffffu) << sh; pa[4 * k + 1] = (pack_bf16(v1[2 * k] * i1, 0.f) & 0xffffu) << sh;
        pa[4 * k + 2] = (pack_bf16(v0[2 * k + 1] * i0, 0.f) & 0xffffu) << sh; pa[4 * k + 3] = (pack_bf16(v1[2 * k + 1] * i1, 0.f) & 0xffffu) << sh;
    }
}
__device__ __forceinline__ void attnB_pv(uint32_t dv, int i, int lane, const uint32_t (&pa)[8], uint32_t (&ob)[6]) {
    const int g = lane >> 2, t = lane & 3;
#pragma unroll
    for (int n = 0; n < 3; n++) {
        float o[4] = {0.f, 0.f, 0.f, 0.f};
#pragma unroll
        for (int k = 0; k < 2; k++) {
            const uint32_t va = dv + (16 * i + 16 * k + 2 * t) * B_PITCH + (8 * n + g) * 2;
            const uint32_t b0 = lds16_n(va) | (lds16_n(va + B_PITCH) << 16), b1 = lds16_n(va + 8 * B_PITCH) | (lds16_n(va + 9 * B_PITCH) << 16);
            mma16816_n(o, pa[4 * k], pa[4 * k + 1], pa[4 * k + 2], pa[4 * k + 3], b0, b1);
        }
        ob[2 * n] = pack_bf16(o[0], o[1]); ob[2 * n + 1] = pack_bf16(o[2], o[3]);
    }
}
#define SPLS 0x111111122888888ull
#define SPL_LAST 16
__host__ __device__ constexpr int spl(int g) { return g == 15 ? SPL_LAST : (int)((SPLS >> (4 * (14 - g))) & 15); }
__host__ __device__ constexpr int slab0(int g) { int n = 0; for (int i = 0; i < g; i++) n += spl(i) > 1 ? spl(i) : 0; return n; }
static_assert(slab0(16) <= 128 && SPL_LAST <= 32, "g_part");
struct Item { int type, mb, nb, k0, nk, half, bpart, slab; };
constexpr uint32_t IFLAG = 1u << 31;
__host__ __device__ constexpr uint32_t mk_item(int type, int mb, int nb, int k0, int nk, int half) {
    return (uint32_t)type | ((uint32_t)mb << 3) | ((uint32_t)nb << 7) | ((uint32_t)k0 << 13) | ((uint32_t)nk << 21) | ((uint32_t)half << 29);
}
constexpr int MAX_LIST = 1536;
struct ItemTab { uint32_t v[MAX_LIST]; unsigned char slab[MAX_LIST]; };
#define LATE_MARGIN 60
#define TAIL_RB 15
#define QP_ROUND 5
#define BP_ROUND 10
#define D_O 2
#define N_EARLY 9
#define N_PRE 0
#define B_PER 3
#define FIN_KB 80
#define F_EARLY 5
constexpr void push_o(ItemTab& t, int& n, int g) {
    const int sp = spl(g);
    if (g == 15) {
        for (int k = 0; k < sp - 1; k++) for (int j = 0; j < 2; j++) { t.slab[n] = slab0(g) + k; t.v[n++] = mk_item(3, g, j, 20 + k * 192 / (sp - 1), (k + 1) * 192 / (sp - 1) - k * 192 / (sp - 1), 2); }
        return;
    }
    for (int k = 0; k < sp; k++)
        for (int j = 0; j < 2; j++) { t.slab[n] = sp == 1 ? 255 : slab0(g) + k; t.v[n++] = mk_item(3, g, j, k * 212 / sp, (k + 1) * 212 / sp - k * 212 / sp, 2); }
}
constexpr void push_bp(ItemTab& t, int& n, int g) {
    for (int j = 0; j < 2; j++) { t.slab[n] = slab0(g) + spl(g) - 1; t.v[n++] = mk_item(3, g, j, 0, 20, 2); }
}
constexpr void push_f(ItemTab& t, int& n, int g) {
    if (spl(g) == 1) return;
    const int lg = spl(g) > FIN_KB / 10 ? 0 : spl(g) > FIN_KB / 20 ? 1 : spl(g) > FIN_KB / 40 ? 2 : 3;
    for (int j = 0; j < (32 >> lg); j++) { t.slab[n] = slab0(g); t.v[n++] = mk_item(4, g, j, lg, spl(g), 2); }
}
constexpr ItemTab build_items() {
    ItemTab t{};
    int n = 0, b1 = 0, at = 0;
    for (; b1 <= B_AHEAD; b1++) for (int j = 0; j < 10; j++) t.v[n++] = mk_item(6, b1, j, 0, 10, 2) | IFLAG;
    for (int r = 0; r < 15; r++) {
        if (r - D_O >= 0 && r - D_O < N_EARLY) push_o(t, n, r - D_O);
        if (r - D_O - F_EARLY >= 0) push_f(t, n, r - D_O - F_EARLY);
        const int b0 = b1;
        for (int i = 0; i < B_PER && b1 < 16; i++, b1++) for (int j = 0; j < 10; j++) t.v[n++] = mk_item(6, b1, j, 0, 10, 2) | IFLAG;
        for (; at < b0; at++) for (int j = 0; j < 8; j++) t.v[n++] = mk_item(1, at, j, 0, 0, 2);
        if (r == BP_ROUND) push_bp(t, n, 15);
        for (int j = 0; j < 32; j++) t.v[n++] = mk_item(5, r, j, 0, 10, 2) | (r >= QPRE ? IFLAG : 0u);
        if (r >= QP_ROUND && QPRE + r - QP_ROUND < 16) for (int j = 0; j < 32; j++) t.v[n++] = mk_item(6, QPRE + r - QP_ROUND, j, 0, 10, 2);
    }
    for (int g = N_EARLY; g < N_EARLY + N_PRE; g++) push_o(t, n, g);
    if (15 >= QPRE) {
        for (int j = 0; j < 32; j++) t.v[n++] = mk_item(5, 15, j, 0, 10, 0) | IFLAG;
        for (int j = 0; j < 32; j++) t.v[n++] = mk_item(5, 15, j, 0, 10, 1) | IFLAG;
    } else {
        for (int j = 0; j < 32; j++) t.v[n++] = mk_item(5, 15, j, 0, 10, 2);
    }
    for (int g = N_EARLY + N_PRE; g < 15; g++) push_o(t, n, g);
    push_o(t, n, 15);
    for (int g = 15 - D_O - F_EARLY; g < 16; g++) push_f(t, n, g);
    while (n < MAX_LIST) t.v[n++] = 7u;
    return t;
}
constexpr int tail_start() {
    const ItemTab t = build_items();
    for (int i = 0; i < MAX_LIST; i++) if ((t.v[i] & 7u) == 5u && ((t.v[i] >> 3) & 15u) == TAIL_RB) return i;
    return MAX_LIST;
}
constexpr int n_items() {
    const ItemTab t = build_items();
    int n = 0;
    while ((t.v[n] & 7u) != 7u) n++;
    return n;
}
constexpr uint32_t N_ITEMS = n_items();
__device__ const ItemTab g_list = build_items();
constexpr int TAIL_START = tail_start();
#define MAX_ITEMS 1536
#define MAX_ITEMS_DEF
#define DEP_OK()
__device__ __forceinline__ Item unpack_item(uint32_t w, uint32_t slab) {
    Item it;
    it.slab = slab & 255;
    it.type = w & 7; it.mb = (w >> 3) & 15; it.nb = (w >> 7) & 63; it.k0 = (w >> 13) & 255; it.nk = (w >> 21) & 255; it.half = (w >> 29) & 3; it.bpart = w >> 31;
    return it;
}
__device__ __forceinline__ void wait_cnt3(unsigned e1, const unsigned* c0, unsigned w0, const unsigned* c1, unsigned w1, const unsigned* c2, unsigned w2) {
    const int lane = threadIdx.x & 31;
    const unsigned* c = lane == 0 ? c0 : lane == 1 ? c1 : lane == 2 ? c2 : nullptr;
    const unsigned want = (lane == 0 ? w0 : lane == 1 ? w1 : w2) * e1;
    int n = 0;
#pragma unroll 1
    while (true) {
        unsigned v = want;
        if (c) asm volatile("ld.acquire.gpu.global.u32 %0, [%1];" : "=r"(v) : "l"(c) : "memory");
        if (__all_sync(0xffffffffu, (int)(v - want) >= 0)) break;
        if (++n > (1 << 22)) { g_err = 5; break; }
        __nanosleep(100);
    }
    __syncwarp();
}
__device__ __forceinline__ void signal_cnt(unsigned* c) { asm volatile("red.release.gpu.global.add.u32 [%0], 1;" :: "l"(c) : "memory"); }

__device__ __forceinline__ float ld_gate(int tok) { float v; asm volatile("ld.global.f32 %0, [%1];" : "=f"(v) : "l"(g_gate + tok) : "memory"); return v; }
template <int NB>
__device__ __forceinline__ void stage_tile_bf16(uint32_t stg, const float* acc, int lane, int w) {
    const uint32_t r = w * 16 + (lane & 7) + ((lane >> 3) & 1) * 8;
#pragma unroll
    for (int i = 0; i < 8 * NB; i += 2) {
        const uint32_t ch = (i & 7) + (lane >> 4);
        stsm4(stg + (i >> 3) * 8192 + r * 128 + ((ch ^ (r & 7)) << 4), pack_bf16(acc[4 * i], acc[4 * i + 1]), pack_bf16(acc[4 * i + 2], acc[4 * i + 3]),
              pack_bf16(acc[4 * i + 4], acc[4 * i + 5]), pack_bf16(acc[4 * i + 6], acc[4 * i + 7]));
    }
}

__device__ __forceinline__ void ldsm4_n(uint32_t& r0, uint32_t& r1, uint32_t& r2, uint32_t& r3, uint32_t a) {
    asm("ldmatrix.sync.aligned.m8n8.x4.shared.b16 {%0,%1,%2,%3}, [%4];" : "=r"(r0), "=r"(r1), "=r"(r2), "=r"(r3) : "r"(a));
}
__device__ __forceinline__ void ldsm4t_n(uint32_t& r0, uint32_t& r1, uint32_t& r2, uint32_t& r3, uint32_t a) {
    asm("ldmatrix.sync.aligned.m8n8.x4.trans.shared.b16 {%0,%1,%2,%3}, [%4];" : "=r"(r0), "=r"(r1), "=r"(r2), "=r"(r3) : "r"(a));
}
__device__ __forceinline__ void ldsm2_n(uint32_t& r0, uint32_t& r1, uint32_t a) {
    asm("ldmatrix.sync.aligned.m8n8.x2.shared.b16 {%0,%1}, [%2];" : "=r"(r0), "=r"(r1) : "r"(a));
}
__device__ __forceinline__ void ldsm2t_n(uint32_t& r0, uint32_t& r1, uint32_t a) {
    asm("ldmatrix.sync.aligned.m8n8.x2.trans.shared.b16 {%0,%1}, [%2];" : "=r"(r0), "=r"(r1) : "r"(a));
}
__device__ __forceinline__ uint32_t dep_on(uint32_t x, uint32_t d) { uint32_t r; asm volatile("{ .reg .u32 t; and.b32 t, %2, 0; add.u32 %0, %1, t; }" : "=r"(r) : "r"(x), "r"(d)); return r; }
template <int hf>
__device__ __forceinline__ void attnA_scores(uint32_t kv, const uint32_t (&qa)[48], int lane, float g0, float g1, uint32_t (&pa)[10]) {
    const int g = lane >> 2, t = lane & 3;
    float sc[5][4];
#pragma unroll
    for (int n = 0; n < 5; n++) { sc[n][0] = sc[n][1] = sc[n][2] = sc[n][3] = 0.f; }
    const uint32_t kb = kv + ((lane >> 3) & 1) * 640 + (lane >> 4) * 128 + (lane & 7) * 16;
#pragma unroll
    for (int ks = 0; ks < 12; ks++) {
        uint32_t b0, b1, b2, b3;
        const uint32_t a0 = qa[4 * ks], a1 = qa[4 * ks + 1], a2 = qa[4 * ks + 2], a3 = qa[4 * ks + 3];
        const uint32_t kk = kb + (ks >> 2) * 10240 + (ks & 3) * 1280;
        ldsm4t_n(b0, b1, b2, b3, kk);
        mma16816_n(sc[0], a0, a1, a2, a3, b0, b1); mma16816_n(sc[1], a0, a1, a2, a3, b2, b3);
        if (hf) { ldsm4t_n(b0, b1, b2, b3, kk + 256); mma16816_n(sc[2], a0, a1, a2, a3, b0, b1); mma16816_n(sc[3], a0, a1, a2, a3, b2, b3); }
        ldsm2t_n(b0, b1, kk + 512 - (lane >> 4) * 128);
        mma16816_n(sc[4], a0, a1, a2, a3, b0, b1);
    }
    const int lim = 16 * hf + g - 2 * t;
    float m0 = fmaxf(sc[4][0], sc[4][1]), m1 = fmaxf(sc[4][2], sc[4][3]);
#pragma unroll
    for (int n = 0; n < 4; n++) {
        if (8 * n > lim) sc[n][0] = -3.0e38f;
        if (8 * n + 1 > lim) sc[n][1] = -3.0e38f;
        if (8 * n > lim + 8) sc[n][2] = -3.0e38f;
        if (8 * n + 1 > lim + 8) sc[n][3] = -3.0e38f;
        m0 = fmaxf(m0, fmaxf(sc[n][0], sc[n][1])); m1 = fmaxf(m1, fmaxf(sc[n][2], sc[n][3]));
    }
    m0 = fmaxf(m0, __shfl_xor_sync(0xffffffffu, m0, 1)); m1 = fmaxf(m1, __shfl_xor_sync(0xffffffffu, m1, 1));
    m0 = fmaxf(m0, __shfl_xor_sync(0xffffffffu, m0, 2)); m1 = fmaxf(m1, __shfl_xor_sync(0xffffffffu, m1, 2));
    m0 *= SCALE_A; m1 *= SCALE_A;
    float s0 = 0.f, s1 = 0.f;
#pragma unroll
    for (int n = 0; n < 5; n++) {
        sc[n][0] = ex2(fmaf(fmaxf(sc[n][0], -1.0e30f), SCALE_A, -m0)); sc[n][1] = ex2(fmaf(fmaxf(sc[n][1], -1.0e30f), SCALE_A, -m0));
        sc[n][2] = ex2(fmaf(fmaxf(sc[n][2], -1.0e30f), SCALE_A, -m1)); sc[n][3] = ex2(fmaf(fmaxf(sc[n][3], -1.0e30f), SCALE_A, -m1));
        s0 += sc[n][0] + sc[n][1]; s1 += sc[n][2] + sc[n][3];
    }
    s0 += __shfl_xor_sync(0xffffffffu, s0, 1); s1 += __shfl_xor_sync(0xffffffffu, s1, 1);
    s0 += __shfl_xor_sync(0xffffffffu, s0, 2); s1 += __shfl_xor_sync(0xffffffffu, s1, 2);
    const float i0 = rcp(s0) * g0, i1 = rcp(s1) * g1;
#pragma unroll
    for (int n = 0; n < 5; n++) { pa[2 * n] = pack_bf16(sc[n][0] * i0, sc[n][1] * i0); pa[2 * n + 1] = pack_bf16(sc[n][2] * i1, sc[n][3] * i1); }
}
template <int hf>
__device__ __forceinline__ void attnA_pv(uint32_t kv, uint32_t stg, int w, int lane, const uint32_t (&pa)[10]) {
    const uint32_t vb = kv + 5120 + (lane >> 3) * 128 + (lane & 7) * 16;
    const uint32_t orow = w * 16 + (lane & 7) + ((lane >> 3) & 1) * 8;
    uint32_t ob[48];
#pragma unroll
    for (int sl = 0; sl < 3; sl++) {
#pragma unroll
        for (int dg = 0; dg < 8; dg += 2) {
            float o[2][4];
            uint32_t m0, m1;
            ldsm2_n(m0, m1, kv + 5120 + sl * 10240 + dg * 640 + 512 + ((lane >> 3) & 1) * 640 + (lane & 7) * 16);
#pragma unroll
            for (int j = 0; j < 2; j++) {
                uint32_t b0, b1, b2, b3;
                ldsm4_n(b0, b1, b2, b3, vb + sl * 10240 + (dg + j) * 640);
                o[j][0] = o[j][1] = o[j][2] = o[j][3] = 0.f;
                mma16816_n(o[j], pa[0], pa[1], pa[2], pa[3], b0, b1);
                if (hf) mma16816_n(o[j], pa[4], pa[5], pa[6], pa[7], b2, b3);
                mma1688_n(o[j], pa[8], pa[9], j ? m1 : m0);
            }
            const int q = (sl * 4 + (dg >> 1)) * 4;
            ob[q] = pack_bf16(o[0][0], o[0][1]); ob[q + 1] = pack_bf16(o[0][2], o[0][3]); ob[q + 2] = pack_bf16(o[1][0], o[1][1]); ob[q + 3] = pack_bf16(o[1][2], o[1][3]);
        }
    }
#pragma unroll
    for (int sl = 0; sl < 3; sl++)
#pragma unroll
        for (int dg = 0; dg < 8; dg += 2) {
            const int q = (sl * 4 + (dg >> 1)) * 4;
            stsm4(stg + sl * 8192 + orow * 128 + (((dg + (lane >> 4)) ^ (lane & 7)) << 4), ob[q], ob[q + 1], ob[q + 2], ob[q + 3]);
        }
}

__global__ void __launch_bounds__(384, 1)
aux_kernel(const __grid_constant__ CUtensorMap tm_x, const __grid_constant__ CUtensorMap tm_wqkv, const __grid_constant__ CUtensorMap tm_oB,
           const __grid_constant__ CUtensorMap tm_woB, const __grid_constant__ CUtensorMap tm_oA, const __grid_constant__ CUtensorMap tm_wo,
           const __grid_constant__ CUtensorMap ts_qkv, const __grid_constant__ CUtensorMap ts_out, const __grid_constant__ CUtensorMap tm_oA64, const __grid_constant__ CUtensorMap tm_wq,
           const __grid_constant__ CUtensorMap tm_x64, const __grid_constant__ CUtensorMap tm_qkvB, const __grid_constant__ CUtensorMap ts_oB, const __grid_constant__ CUtensorMap tm_qp, const __grid_constant__ CUtensorMap ts_part,
           bf16* __restrict__ out) {
    extern __shared__ __align__(1024) char smem_raw[];
    const uint32_t sb = smem_u32(smem_raw);
    const uint32_t bar = sb + G_OUT + 2 * STG_BYTES;
    if (threadIdx.x == 0) {
        for (int i = 0; i < 8; i++) { mbar_init(bar + 8 * i, 1); mbar_init(bar + 64 + 8 * i, 8); }
        for (int i = 0; i < 2; i++) {
            mbar_init(bar + 128 + 8 * i, 1); mbar_init(bar + 144 + 8 * i, 2);
            mbar_init(bar + 224 + 8 * i, 128); mbar_init(bar + 240 + 8 * i, 1);
        }
        asm volatile("fence.mbarrier_init.release.cluster;" ::: "memory");
    }
    __syncthreads();
    const int wid = __shfl_sync(0xffffffffu, (int)(threadIdx.x >> 5), 0), wg = wid >> 2;
    if (wg == 2) {
        asm volatile("setmaxnreg.dec.sync.aligned.u32 40;");
        const bool lead = elect_one();
        if (wid == 8) {
            const uint64_t pol = pol_stream();
            uint32_t seq = 0, tail = 0, cur = 0, used = 0;
            uint64_t alloc = 0;
#define RING_ACQ(size) \
                uint32_t pad_ = cur + (size) > RING_CAP ? RING_CAP - cur : 0u; \
                if (cur + (size) > RING_CAP) cur = 0; \
                while ((used + pad_ + (size) > RING_CAP || seq - tail >= 8u) && tail != seq) { \
                    mbar_wait(bar + 64 + 8 * (tail & 7u), (tail >> 3) & 1u); \
                    used -= (uint32_t)((alloc >> (8 * (tail & 7u))) & 255u) << 10; tail++; } \
                if (tail == seq) pad_ = 0; \
                alloc = (alloc & ~(255ull << (8 * (seq & 7u)))) | ((uint64_t)((pad_ + (size)) >> 10) << (8 * (seq & 7u))); \
                used += pad_ + (size); \
                const uint32_t d = sb + cur, fb = bar + 8 * (seq & 7u)
#define RING_ADV(size) { cur += (size); seq++; }
            uint32_t nidx = 0;
#define REQ_NOW() { if (lead) nidx = (uint32_t)atomicAdd(&g_ctl.next, 1ull) & 2047u; }
#define REQ_NEXT() { if (!late) REQ_NOW(); }
#define REQ_PEEK() { late = late || (ld_relaxed1(&g_ctl.next) & 2047u) + LATE_MARGIN >= (uint32_t)TAIL_START; late = __any_sync(0xffffffffu, late); }
            bool late = false;
            uint32_t e1 = 0;
            if (lead) { const unsigned long long tk = atomicAdd(&g_ctl.next, 1ull); nidx = (uint32_t)tk & 2047u; e1 = (uint32_t)(tk >> 11) + 1u; }
            e1 = __reduce_or_sync(0xffffffffu, e1);
            for (int n = 0;; n++) {
                if (late) {
                    while (tail != seq) { mbar_wait(bar + 64 + 8 * (tail & 7u), (tail >> 3) & 1u); used -= (uint32_t)((alloc >> (8 * (tail & 7u))) & 255u) << 10; tail++; }
                    REQ_NOW();
                }
                const uint32_t gidx = __reduce_max_sync(0xffffffffu, nidx);
                late = gidx + LATE_MARGIN >= (uint32_t)TAIL_START;
                nidx = 0;
                const uint32_t nw = __shfl_sync(0xffffffffu, gidx < MAX_LIST ? g_list.v[gidx] : 7u, 0);
                const uint32_t nsl = __shfl_sync(0xffffffffu, gidx < MAX_LIST ? (uint32_t)g_list.slab[gidx] : 0u, 0) | (gidx << 8);
                const Item it = unpack_item(nw, nsl);
                if (n >= 2) mbar_wait(bar + 144 + 8 * (n & 1), ((n >> 1) - 1) & 1);
                if (lead) { sts64(bar + 160 + 8 * (n & 1), nw, nsl); mbar_arrive(bar + 128 + 8 * (n & 1)); }
                if (it.type == 7) {
                    if (lead && gidx == N_ITEMS) atomicAdd(&g_ctl.next, (unsigned long long)(2048 - N_ITEMS - gridDim.x));
                    break;
                }
                if (it.type == 1) {
                    wait_cnt3(e1, &g_ctl.b1[it.mb], 20, it.mb > 0 && it.nb < 4 ? &g_ctl.b1[it.mb - 1] : nullptr, 20, &g_ctl.gate, 512);
                    asm volatile("fence.proxy.async.global;" ::: "memory");
                    for (int p = 0; p < 3; p++) {
                        RING_ACQ(SZ_B);
                        if (lead) { mbar_expect(fb, 80 * 336); tma2d_s(d, &tm_qkvB, p * 640 + (it.nb & 3) * 160, it.mb * 128 + (it.nb >> 2) * 64 - 14, fb, pol); }
                        RING_ADV(SZ_B);
                    }
                    REQ_NEXT();
                    continue;
                }
                if (it.type == 5 || it.type == 6) {
                    const CUtensorMap* ta = it.half == 2 ? &tm_x : &tm_x64;
                    const int arow = it.mb * 128 + (it.half == 1 ? 64 : 0), bcol = it.nb * 192;
                    const uint32_t aoff = it.half == 1 ? 8192 : 0, bytes = it.half == 2 ? 40960 : 32768;
                    const CUtensorMap* tbq = it.type == 6 && it.bpart ? &tm_wqkv : &tm_wq;
                    if (it.type == 5 && it.bpart) {
                        wait_cnt3(e1, &g_ctl.qp[it.mb - QPRE], 64, it.half != 1 ? &g_ctl.seg[it.mb * 2] : nullptr, 2 * NCTA, it.half != 0 ? &g_ctl.seg[it.mb * 2 + 1] : nullptr, 2 * NCTA);
                        DEP_OK()
                        asm volatile("fence.proxy.async.global;" ::: "memory");
                        RING_ACQ(SZ_QP);
                        if (lead) {
                            mbar_expect(fb, it.half == 2 ? 49152 : 24576);
                            for (int h = (it.half == 1); h <= (it.half != 0); h++)
#pragma unroll
                                for (int c = 0; c < 3; c++) tma2d(d + h * 24576 + c * 8192, &tm_qp, bcol + c * 64, (it.mb - QPRE) * 128 + h * 64, fb);
                        }
                        RING_ADV(SZ_QP);
                    } else
                    for (int k = 0; k < 640; k += 64) {
                        if (it.type == 6 && k == 192) REQ_NEXT();
                        RING_ACQ(SZ_Q);
                        if (lead) {
                            mbar_expect(fb, bytes);
                            tma2d(d + aoff, ta, k, arow, fb);
#pragma unroll
                            for (int c = 0; c < 3; c++) tma2d(d + 16384 + c * 8192, tbq, bcol + c * 64, k, fb);
                        }
                        RING_ADV(SZ_Q);
                    }
                    if (it.type == 6) continue;
                    if (!it.bpart) {
                        wait_cnt3(e1, it.half != 1 ? &g_ctl.seg[it.mb * 2] : nullptr, 2 * NCTA, it.half != 0 ? &g_ctl.seg[it.mb * 2 + 1] : nullptr, 2 * NCTA, &g_ctl.gate, 512);
                        DEP_OK()
                        asm volatile("fence.proxy.async.global;" ::: "memory");
                    }
                    REQ_NEXT();
                    for (int j = (it.half == 1 ? 2 : 0); j < (it.half == 0 ? 2 : 4); j++) {
                        const char* kv = g_kv + (size_t)((it.mb * 4 + j) * NCTA + it.nb * 3) * 10240;
                        RING_ACQ(SZ_KV);
                        if (lead) { mbar_expect(fb, 30720); bulk_g2s_s(d, kv, 30720, fb, pol); }
                        RING_ADV(SZ_KV);
                    }
                    continue;
                }
                if (it.type == 4) {
                    REQ_NEXT();
                    const uint32_t bytes = 5120u << it.k0;
                    wait_cnt3(e1, &g_ctl.fin[it.mb * 2 + ((it.nb << it.k0) >> 4)], 2 * it.nk, nullptr, 0, nullptr, 0);
                    DEP_OK()
                    asm volatile("fence.proxy.async.global;" ::: "memory");
                    const char* src = (const char*)g_part + (size_t)it.slab * (128 * DM * 2) + it.nb * bytes;
                    RING_ACQ(bytes * it.nk);
                    if (lead) {
                        mbar_expect(fb, bytes * it.nk);
#pragma unroll 1
                        for (int p = 0; p < it.nk; p++) bulk_g2s_s(d + p * bytes, src + p * (128 * DM * 2), bytes, fb, pol);
                    }
                    RING_ADV(bytes * it.nk);
                    continue;
                }
                const int kend = it.k0 + it.nk, kreq = kend - (it.nk < REQ_AHEAD ? it.nk : REQ_AHEAD);
                if (it.k0 < 20) {
                    wait_cnt3(e1, &g_ctl.at[it.mb], 16, nullptr, 0, nullptr, 0);
                    asm volatile("fence.proxy.async.global;" ::: "memory");
                }
                for (int k = it.k0; k < kend; k++) {
                    if (k == (it.k0 < 20 ? 20 : it.k0)) {
                        wait_cnt3(e1, &g_ctl.ata[it.mb * 2], 32, &g_ctl.ata[it.mb * 2 + 1], 32, nullptr, 0);
                        DEP_OK()
                        asm volatile("fence.proxy.async.global;" ::: "memory");
                    }
                    if (k == kreq) { REQ_PEEK(); REQ_NEXT(); }
                    const CUtensorMap* ta = k < 20 ? &tm_oB : &tm_oA;
                    const CUtensorMap* tb = k < 20 ? &tm_woB : &tm_wo;
                    const int kk = (k < 20 ? k : k - 20) * 32;
                    RING_ACQ(SZ_O);
                    if (lead) {
                        mbar_expect(fb, SZ_O);
                        tma2d_s(d, ta, kk, it.mb * 128, fb, pol);
                        asm volatile("cp.async.bulk.tensor.3d.shared::cluster.global.mbarrier::complete_tx::bytes [%0], [%1, {0, %3, %4}], [%2];"
                                     :: "r"(d + 8192), "l"(tb), "r"(fb), "r"(kk), "r"(it.nb * 5) : "memory");
                    }
                    RING_ADV(SZ_O);
                }
            }
#undef RING_ACQ
#undef RING_ADV
#undef REQ_NEXT
#undef REQ_PEEK
#undef REQ_NOW
        } else if (wid < 11) {
            const int sw = wid - 9;
            const uint32_t stg = sb + G_OUT + sw * STG_BYTES;
            const uint64_t spol = pol_stream();
            for (uint32_t ph = 0;; ph ^= 1) {
                mbar_wait(bar + 224 + 8 * sw, ph);
                const uint4 mv = lds128(bar + 256 + 16 * sw);
                const int kind = __shfl_sync(0xffffffffu, (int)mv.x, 0), col = __shfl_sync(0xffffffffu, (int)mv.y, 0), row = __shfl_sync(0xffffffffu, (int)mv.z, 0);
                const int cnt = __shfl_sync(0xffffffffu, (int)mv.w, 0);
                if (kind < 0) break;
                const int kd = kind & 15, nbox = kind >> 4;
                const CUtensorMap* tm = kd == 7 ? &ts_qkv : kd == 2 ? &ts_out : kd == 5 ? &ts_part : kd == 3 ? &tm_oA64 : kd == 6 ? &tm_qp : &ts_oB;
                if (lead) {
                    for (int b = 0; b < nbox; b++) {
                        if (kd == 2) asm volatile("cp.async.bulk.tensor.2d.global.shared::cta.bulk_group.L2::cache_hint [%0, {%2, %3}], [%1], %4;" :: "l"(tm), "r"(stg + b * 8192), "r"(col + b * 64), "r"(row), "l"(spol) : "memory");
                        else asm volatile("cp.async.bulk.tensor.2d.global.shared::cta.bulk_group [%0, {%2, %3}], [%1];" :: "l"(tm), "r"(stg + b * 8192), "r"(col + b * 64), "r"(row) : "memory");
                    }
                    asm volatile("cp.async.bulk.commit_group;" ::: "memory");
                    asm volatile("cp.async.bulk.wait_group.read 0;" ::: "memory");
                    mbar_arrive(bar + 240 + 8 * sw);
                    asm volatile("cp.async.bulk.wait_group 0;" ::: "memory");
                    if (cnt >= 0) signal_cnt((unsigned*)&g_ctl + cnt);
                }
                __syncwarp();
            }
        }
        asm volatile("griddepcontrol.wait;" ::: "memory");
    } else {
        asm volatile("setmaxnreg.inc.sync.aligned.u32 232;");
        const int lane = threadIdx.x & 31, w = wid & 3, g = lane >> 2, t = lane & 3;
        const uint32_t stg = sb + G_OUT + wg * STG_BYTES;
        uint32_t seq_o = 0, cur_o = 0;
        uint32_t n_st = 0, n_free = 0;
#define RING_WAIT(size) { if (cur + (size) > RING_CAP) cur = 0; mbar_wait(bar + 8 * (seq & 7u), (seq >> 3) & 1u); }
#define RING_ADV(size) { cur += (size); seq++; }
#define RING_FREE(sq) mbar_arrive(bar + 64 + 8 * ((sq) & 7u))
#define RING_SAVE() { seq_o = seq; cur_o = cur; }
#define STG_ACQ() if (n_free != n_st) { mbar_wait(bar + 240 + 8 * wg, n_free & 1); n_free++; }
#define STG_IDX()
#define STG_POST(kind, col, row, cnt) { STG_IDX() if ((threadIdx.x & 127) == 0) sts128(bar + 256 + 16 * wg, make_uint4((uint32_t)(kind), (uint32_t)(col), (uint32_t)(row), (uint32_t)(cnt))); \
                                        fence_async_smem(); mbar_arrive(bar + 224 + 8 * wg); n_st++; }
#define GEMM_STAGE(FN, acc, FIRST, size) { \
                    RING_WAIT(size); \
                    const uint32_t d = sb + cur; \
                    const uint64_t da = make_desc(d + wg * 8192, 16, 1024, 1), db = make_desc(d + 16384, 8192, 1024, 1); \
                    wg_fence(); \
                    if (FIRST) FN##_first(acc, da, db); else FN(acc, da, db, 1); \
                    _Pragma("unroll") for (int kk = 1; kk < 4; kk++) FN(acc, da + kk * 2, db + kk * 128, 1); \
                    wg_commit(); }
#define GEMM_LOOP(FN, acc, nks, size) { \
                GEMM_STAGE(FN, acc, true, size) \
                RING_ADV(size); \
                for (int k = 1; k < (nks); k++) { \
                    GEMM_STAGE(FN, acc, false, size) \
                    wg_wait<1>(); \
                    if (lane == 0) RING_FREE(seq - 1); \
                    RING_ADV(size); \
                } \
                wg_wait<0>(); \
                if (lane == 0) RING_FREE(seq - 1); }
        for (int n = 0;; n++) {
            mbar_wait(bar + 128 + 8 * (n & 1), (n >> 1) & 1);
            const uint32_t iw = __shfl_sync(0xffffffffu, lds32(bar + 160 + 8 * (n & 1)), 0);
            const uint32_t isl = __shfl_sync(0xffffffffu, lds32(bar + 164 + 8 * (n & 1)), 0);
            bar_sync(1 + wg, 128);
            if ((threadIdx.x & 127) == 0) mbar_arrive(bar + 144 + 8 * (n & 1));
            const Item it = unpack_item(iw, isl);
            if (it.type == 7) { STG_ACQ(); STG_POST(-1, 0, 0, -1); break; }
            uint32_t seq = (uint32_t)opaque((int)seq_o), cur = (uint32_t)opaque((int)cur_o);
            if (it.type == 1) {
                const int t0 = it.mb * 128 + (it.nb >> 2) * 64;
                RING_WAIT(SZ_B);
                const uint32_t s0 = cur;
                RING_ADV(SZ_B);
                RING_WAIT(SZ_B);
                const uint32_t s1 = cur;
                RING_ADV(SZ_B);
                float gb[8];
#pragma unroll
                for (int i = 0; i < 8; i++) gb[i] = 1.f - ld_gate(t0 + 8 * i + g);
                uint32_t pa[4][8];
                const uint32_t dq = (uint32_t)opaque((int)(sb + s0 + wid * 40)), dk = (uint32_t)opaque((int)(sb + s1 + wid * 40));
                if (t0 == 0) attnB_scores<true>(dq, dk, 0, t0, lane, gb[0], gb[1], pa[0]); else attnB_scores<false>(dq, dk, 0, t0, lane, gb[0], gb[1], pa[0]);
#pragma unroll
                for (int i = 1; i < 4; i++) attnB_scores<false>(dq, dk, i, t0, lane, gb[2 * i], gb[2 * i + 1], pa[i]);
                asm volatile("" :: "r"(pa[0][0]), "r"(pa[1][0]), "r"(pa[2][0]), "r"(pa[3][0]) : "memory");
                __syncwarp();
                if (lane == 0) { RING_FREE(seq - 2); RING_FREE(seq - 1); }
                STG_ACQ();
                bar_sync(3, 256);
                RING_WAIT(SZ_B);
                const uint32_t dv = (uint32_t)opaque((int)(sb + cur + wid * 40));
                uint32_t ob[4][6];
#pragma unroll
                for (int i = 0; i < 4; i++) attnB_pv(dv, i, lane, pa[i], ob[i]);
#pragma unroll
                for (int i = 0; i < 4; i++) {
                    const uint32_t out = sb + G_OUT + (i >> 1) * STG_BYTES + (i & 1) * 16 * 320 + wid * 40 + g * 320 + t * 4;
#pragma unroll
                    for (int n = 0; n < 3; n++)
                        if (n < 2 || t < 2) { sts32(out + n * 16, ob[i][2 * n]); sts32(out + 8 * 320 + n * 16, ob[i][2 * n + 1]); }
                }
                __syncwarp();
                if (lane == 0) RING_FREE(seq);
                RING_ADV(SZ_B);
                RING_SAVE();
                fence_async_smem();
                bar_sync(3, 256);
                STG_POST(4 + 16, (it.nb & 3) * 160, t0 + wg * 32, (int)(offsetof(AuxCtl, at) / 4) + it.mb);
                continue;
            }
            const bool active = it.half == 2 || it.half == wg;
            if (!active) {
                const int nq = it.bpart ? 1 : 10;
                for (int k = 0; k < nq + 2; k++) {
                    const uint32_t sz = k < nq ? (it.bpart ? SZ_QP : SZ_Q) : SZ_KV;
                    RING_WAIT(sz);
                    if (lane == 0) RING_FREE(seq);
                    RING_ADV(sz);
                }
                RING_SAVE();
                continue;
            }
            if (it.type == 6) {
                float acc[96];
                GEMM_LOOP(wgmma_ss_n192_tb, acc, 10, SZ_Q)
                RING_SAVE();
                STG_ACQ();
                const uint32_t r = w * 16 + (lane & 7) + ((lane >> 3) & 1) * 8;
#pragma unroll
                for (int i = 0; i < 24; i += 2) {
                    const uint32_t ch = (i & 7) + (lane >> 4);
                    stsm4(stg + (i >> 3) * 8192 + r * 128 + ((ch ^ (r & 7)) << 4), pack_bf16(acc[4 * i], acc[4 * i + 1]), pack_bf16(acc[4 * i + 2], acc[4 * i + 3]),
                          pack_bf16(acc[4 * i + 4], acc[4 * i + 5]), pack_bf16(acc[4 * i + 6], acc[4 * i + 7]));
                }
                if (it.bpart) STG_POST(7 + 48, it.nb * 192, it.mb * 128 + wg * 64, (int)(offsetof(AuxCtl, b1) / 4) + it.mb)
                else STG_POST(6 + 48, it.nb * 192, (it.mb - QPRE) * 128 + wg * 64, (int)(offsetof(AuxCtl, qp) / 4) + it.mb - QPRE)
                continue;
            }
            if (it.type == 5) {
                uint32_t qa[48];
                if (it.bpart) {
                    RING_WAIT(SZ_QP);
                    const uint32_t r = w * 16 + (lane & 7) + ((lane >> 3) & 1) * 8, qs = sb + cur + wg * 24576 + r * 128;
#pragma unroll
                    for (int ks = 0; ks < 12; ks++)
                        ldsm4(qa[4 * ks], qa[4 * ks + 1], qa[4 * ks + 2], qa[4 * ks + 3], qs + (ks >> 2) * 8192 + (((2 * (ks & 3) + (lane >> 4)) ^ (r & 7)) << 4));
                    asm volatile("" :: "r"(qa[0]), "r"(qa[47]) : "memory");
                    __syncwarp();
                    if (lane == 0) RING_FREE(seq);
                    RING_ADV(SZ_QP);
                } else {
                    float acc[96];
                    GEMM_LOOP(wgmma_ss_n192_tb, acc, 10, SZ_Q)
#pragma unroll
                    for (int i = 0; i < 48; i++) qa[i] = pack_bf16(acc[2 * i], acc[2 * i + 1]);
                }
                STG_ACQ();
                const int own = 2 * wg + (w >> 1);
                for (int j = (it.half == 1 ? 2 : 0); j < (it.half == 0 ? 2 : 4); j++) {
                    RING_WAIT(SZ_KV);
                    if (j == own) {
                        uint32_t pa[10];
                        const uint32_t kv = (uint32_t)opaque((int)(sb + cur));
                        const float g0 = ld_gate(it.mb * 128 + wid * 16 + g), g1 = ld_gate(it.mb * 128 + wid * 16 + g + 8);
                        if (w & 1) { attnA_scores<1>(kv, qa, lane, g0, g1, pa); attnA_pv<1>(dep_on(kv, pa[0]), stg, w, lane, pa); }
                        else { attnA_scores<0>(kv, qa, lane, g0, g1, pa); attnA_pv<0>(dep_on(kv, pa[0]), stg, w, lane, pa); }
                    }
                    __syncwarp();
                    if (lane == 0) RING_FREE(seq);
                    RING_ADV(SZ_KV);
                }
                RING_SAVE();
                STG_POST(3 + 48, it.nb * 192, it.mb * 128 + wg * 64, (int)(offsetof(AuxCtl, ata) / 4) + it.mb * 2 + wg);
                continue;
            }
            if (it.type == 4) {
                const uint32_t bytes = 5120u << it.k0;
                RING_WAIT(bytes * it.nk);
                char* o = (char*)out + (size_t)it.mb * (128 * DM * 2) + it.nb * bytes;
#pragma unroll 1
                for (uint32_t c = threadIdx.x * 8; c < bytes; c += 4096) {
                    float a[8] = {0.f, 0.f, 0.f, 0.f, 0.f, 0.f, 0.f, 0.f};
                    const uint32_t c2 = c + 2048 < bytes ? 2048u : 0u;
#pragma unroll 1
                    for (int p = 0; p < it.nk; p += 4) {
                        uint2 u[8];
#pragma unroll
                        for (int i = 0; i < 4; i++) {
                            const uint32_t ad = sb + cur + min(p + i, it.nk - 1) * bytes + c;
                            u[i] = lds64(ad); u[4 + i] = lds64(ad + c2);
                        }
#pragma unroll
                        for (int i = 0; i < 8; i++) {
                            const float m = p + (i & 3) < it.nk ? 1.f : 0.f;
                            float* b = &a[i & 4];
                            b[0] = fmaf(bf_lo(u[i].x), m, b[0]); b[1] = fmaf(bf_hi(u[i].x), m, b[1]); b[2] = fmaf(bf_lo(u[i].y), m, b[2]); b[3] = fmaf(bf_hi(u[i].y), m, b[3]);
                        }
                    }
                    *(uint2*)(o + c) = make_uint2(pack_bf16(a[0], a[1]), pack_bf16(a[2], a[3]));
                    *(uint2*)(o + c + c2) = make_uint2(pack_bf16(a[4], a[5]), pack_bf16(a[6], a[7]));
                }
                __syncwarp();
                if (lane == 0) RING_FREE(seq);
                RING_ADV(bytes * it.nk);
                RING_SAVE();
                continue;
            }
            float acc[160];
#define O_STAGE(FIRST) { \
                RING_WAIT(SZ_O); \
                const uint32_t d = sb + cur; \
                const uint64_t da = make_desc(d + wg * 4096, 16, 512, 2), db = make_desc(d + 8192, 4096, 1024, 1); \
                wg_fence(); \
                if (FIRST) { wgmma_ss_n192_tb_first(acc, da, db); wgmma_ss_n128_tb_first(acc + 96, da, db + 768); } \
                else { wgmma_ss_n192_tb(acc, da, db, 1); wgmma_ss_n128_tb(acc + 96, da, db + 768, 1); } \
                wgmma_ss_n192_tb(acc, da + 2, db + 128, 1); wgmma_ss_n128_tb(acc + 96, da + 2, db + 768 + 128, 1); \
                wg_commit(); }
            O_STAGE(true)
            RING_ADV(SZ_O);
            for (int k = 1; k < it.nk; k++) {
                O_STAGE(false)
                wg_wait<1>();
                if (lane == 0) RING_FREE(seq - 1);
                RING_ADV(SZ_O);
            }
            wg_wait<0>();
            if (lane == 0) RING_FREE(seq - 1);
#undef O_STAGE
            RING_SAVE();
            const int kind = it.slab == 255 ? 2 : 5, row = (it.slab == 255 ? it.mb : it.slab) * 128 + wg * 64;
            STG_ACQ();
            stage_tile_bf16<3>(stg, acc, lane, w);
            STG_POST(kind + 48, it.nb * 320, row, -1)
            STG_ACQ();
            stage_tile_bf16<2>(stg, acc + 96, lane, w);
            STG_POST(kind + 32, it.nb * 320 + 192, row, it.slab == 255 ? -1 : (int)(offsetof(AuxCtl, fin) / 4) + it.mb * 2 + wg)
        }
#undef GEMM_LOOP
#undef GEMM_STAGE
#undef RING_WAIT
#undef RING_ADV
#undef RING_FREE
#undef RING_SAVE
#undef STG_ACQ
#undef STG_POST
        asm volatile("griddepcontrol.wait;" ::: "memory");
    }
}

typedef CUresult (*EncodeFn)(CUtensorMap*, CUtensorMapDataType, cuuint32_t, void*, const cuuint64_t*, const cuuint64_t*,
                             const cuuint32_t*, const cuuint32_t*, CUtensorMapInterleave, CUtensorMapSwizzle,
                             CUtensorMapL2promotion, CUtensorMapFloatOOBfill);

static CUtensorMap make_map3(EncodeFn fn, const void* ptr, uint64_t rows) {
    CUtensorMap m;
    cuuint64_t dims[3] = {64, rows, 10}, strides[2] = {DM * 2, 128};
    cuuint32_t box[3] = {64, 32, 5}, es[3] = {1, 1, 1};
    fn(&m, CU_TENSOR_MAP_DATA_TYPE_BFLOAT16, 3, (void*)ptr, dims, strides, box, es, CU_TENSOR_MAP_INTERLEAVE_NONE, CU_TENSOR_MAP_SWIZZLE_128B,
       CU_TENSOR_MAP_L2_PROMOTION_L2_128B, CU_TENSOR_MAP_FLOAT_OOB_FILL_NONE);
    return m;
}
static CUtensorMap make_map(EncodeFn fn, const void* ptr, uint64_t cols, uint64_t rows, uint32_t bc, uint32_t br, bool f32 = false, bool swz = true) {
    CUtensorMap m;
    cuuint64_t dims[2] = {cols, rows};
    cuuint64_t strides[1] = {cols * (f32 ? 4 : 2)};
    cuuint32_t box[2] = {bc, br};
    cuuint32_t es[2] = {1, 1};
    fn(&m, f32 ? CU_TENSOR_MAP_DATA_TYPE_FLOAT32 : CU_TENSOR_MAP_DATA_TYPE_BFLOAT16, 2, (void*)ptr, dims, strides, box, es, CU_TENSOR_MAP_INTERLEAVE_NONE,
       !swz ? CU_TENSOR_MAP_SWIZZLE_NONE : bc == 32 ? CU_TENSOR_MAP_SWIZZLE_64B : CU_TENSOR_MAP_SWIZZLE_128B, CU_TENSOR_MAP_L2_PROMOTION_L2_128B, CU_TENSOR_MAP_FLOAT_OOB_FILL_NONE);
    return m;
}

extern "C" void kernel_launch(void* const* d_in, const int* in_sizes, int n_in, void* d_out, int out_size) {
    const bf16* x = (const bf16*)d_in[0];
    const bf16* mem0 = (const bf16*)d_in[1];
    const bf16* Wq = (const bf16*)d_in[2];
    const bf16* Wk = (const bf16*)d_in[3];
    const bf16* Wv = (const bf16*)d_in[4];
    const bf16* Wo = (const bf16*)d_in[5];
    const bf16* wqkv = (const bf16*)d_in[8];
    const bf16* wo = (const bf16*)d_in[9];
    const bf16* gate_w = (const bf16*)d_in[10];
    bf16* out = (bf16*)d_out;

    static EncodeFn fn = nullptr;
    static int n_aux = 36;
    static void *p_acc, *p_oA, *p_qkvB, *p_oB, *p_Qp;
    if (!fn) {
        cudaDriverEntryPointQueryResult qr;
        void* f = nullptr;
        cudaGetDriverEntryPoint("cuTensorMapEncodeTiled", &f, cudaEnableDefault, &qr);
        fn = (EncodeFn)f;
        cudaGetSymbolAddress(&p_acc, g_part); cudaGetSymbolAddress(&p_oA, g_oA); cudaGetSymbolAddress(&p_qkvB, g_qkvB); cudaGetSymbolAddress(&p_oB, g_oB); cudaGetSymbolAddress(&p_Qp, g_Qp);
        int sms = 132;
        cudaDeviceGetAttribute(&sms, cudaDevAttrMultiProcessorCount, 0);
        n_aux = sms;
        cudaFuncSetAttribute(rec_kernel, cudaFuncAttributeMaxDynamicSharedMemorySize, REC_SMEM_L);
        cudaFuncSetAttribute(aux_kernel, cudaFuncAttributeMaxDynamicSharedMemorySize, GEMM_SMEM);
    }
    const CUtensorMap tm_x32 = make_map3(fn, x, S_LEN);
    const CUtensorMap tm_wq = make_map(fn, Wq, HD, DM, 64, 128);
    const CUtensorMap tm_wk = make_map(fn, Wk, HD, DM, 64, 128);
    const CUtensorMap tm_wv = make_map(fn, Wv, HD, DM, 64, 128);
    const CUtensorMap tm_wo = make_map(fn, Wo, DM, HD, 64, 64);
    const CUtensorMap tm_x128 = make_map(fn, x, DM, S_LEN, 64, 128);
    const CUtensorMap tm_wqkv = make_map(fn, wqkv, 3 * DM, DM, 64, 64);
    const CUtensorMap tm_oB = make_map(fn, p_oB, DM, S_LEN, 32, 128);
    const CUtensorMap tm_woB = make_map3(fn, wo, DM);
    const CUtensorMap tm_oA = make_map(fn, p_oA, HD, S_LEN, 32, 128);

    rec_kernel<<<NCTA, 384, REC_SMEM_L, cudaStreamPerThread>>>(tm_x32, tm_wq, tm_wk, tm_wv, tm_wo, mem0, x, gate_w);
    cudaLaunchConfig_t cfg = {};
    cfg.gridDim = dim3(n_aux); cfg.blockDim = dim3(384); cfg.dynamicSmemBytes = GEMM_SMEM; cfg.stream = cudaStreamPerThread;
    cudaLaunchAttribute at[1];
    at[0].id = cudaLaunchAttributeProgrammaticStreamSerialization; at[0].val.programmaticStreamSerializationAllowed = 1;
    cfg.attrs = at; cfg.numAttrs = 1;
    const CUtensorMap ts_qkv = make_map(fn, p_qkvB, 3 * DM, S_LEN, 64, 64), ts_out = make_map(fn, out, DM, S_LEN, 64, 64);
    cudaLaunchKernelEx(&cfg, aux_kernel, tm_x128, tm_wqkv, tm_oB, tm_woB, tm_oA, make_map3(fn, Wo, HD), ts_qkv, ts_out, make_map(fn, p_oA, HD, S_LEN, 64, 64),
                       make_map(fn, Wq, HD, DM, 64, 64), make_map(fn, x, DM, S_LEN, 64, 64), make_map(fn, p_qkvB, 3 * DM, S_LEN, 168, 80, false, false),
                       make_map(fn, p_oB, DM, S_LEN, 160, 32, false, false), make_map(fn, p_Qp, HD, 256, 64, 64), make_map(fn, p_acc, DM, 128 * 128, 64, 64), out);
}
```
